```python
import torch

def _softmax(x, axis=-1):
    return torch.softmax(x, dim=axis)
def _gelu(x):
    return torch.nn.functional.gelu(x, approximate="tanh")
def _silu(x):
    return torch.nn.functional.silu(x)
def _sigmoid(x):
    return torch.sigmoid(x)
def _layernorm(x, axis=-1, eps=1e-5):
    m = x.mean(dim=axis, keepdim=True)
    v = x.var(dim=axis, keepdim=True, unbiased=False)
    return (x - m) / torch.sqrt(v + eps)
def _scatter_add(tgt, idx, src, axis=0):
    return tgt.clone().index_add_(axis, idx, src)
def _segment_sum(src, seg, n):
    out = torch.zeros((n,) + src.shape[1:], dtype=src.dtype)
    return out.index_add_(0, seg, src)
def _pad(x, pw):
    flat = tuple(v for pair in reversed(pw) for v in pair)
    return torch.nn.functional.pad(x, flat)

kernel_name = 'recurrent_scan__compressed_kv_cla__dense_activation_relu__prompt'

def setup_inputs():

    _w = (lambda a: (lambda t: t.to(torch.bfloat16) if t.is_floating_point() else t)(torch.as_tensor(a)))
    def _A_setup():
        B, H, Sq, Sk, D, M = 1, 32, 2048, 2048, 128, 512
        Dc = 4 * D
        return {
            "x": _w((lambda *s: torch.randn(*s, dtype=torch.bfloat16) * 0.05)(B, Sq, M)),
            "c_kv": _w((lambda *s: torch.randn(*s, dtype=torch.bfloat16) * 0.2)(B, Sk, Dc)),
            "w_q": _w((lambda *s: torch.randn(*s, dtype=torch.bfloat16) * 3.2)(M, H, D) * (M ** -0.5)),
            "w_uk": _w((lambda *s: torch.randn(*s, dtype=torch.bfloat16) * 3.2)(Dc, H, D) * (Dc ** -0.5)),
            "w_uv": _w((lambda *s: torch.randn(*s, dtype=torch.bfloat16) * 0.2)(Dc, H, D) * (Dc ** -0.5)),
            "w_o": _w((lambda *s: torch.randn(*s, dtype=torch.bfloat16) * 0.2)(H, D, M) * ((H * D) ** -0.5)),
        }
    _A_in = _A_setup()

    def _B_setup():
        B, S, D, Dff = 1, 2048, 512, 1792
        return {
            "x": _w((lambda *s: torch.randn(*s, dtype=torch.bfloat16) * 0.05)(B, S, D)),
            "w1": _w((lambda *s: torch.randn(*s, dtype=torch.bfloat16) * 0.1)(D, Dff)),
            "w2": _w((lambda *s: torch.randn(*s, dtype=torch.bfloat16) * 0.1)(Dff, D)),
        }
    _B_in = _B_setup()

    return {
        "A_x": _A_in["x"],
        "A_c_kv": _A_in["c_kv"],
        "A_w_q": _A_in["w_q"],
        "A_w_uk": _A_in["w_uk"],
        "A_w_uv": _A_in["w_uv"],
        "A_w_o": _A_in["w_o"],
        "B_x": _B_in["x"],
        "B_w1": _B_in["w1"],
        "B_w2": _B_in["w2"],
    }

def reference(A_x, A_c_kv, A_w_q, A_w_uk, A_w_uv, A_w_o, B_x, B_w1, B_w2):
    def _A_ref(x, c_kv, w_q, w_uk, w_uv, w_o):
        B, Sq, M = x.shape[0], x.shape[1], x.shape[2]
        Sk = c_kv.shape[1]
        H, D = w_q.shape[1], w_q.shape[2]
        q = torch.einsum("bqm,mhd->bhqd", x, w_q)
        k = torch.einsum("bkc,chd->bhkd", c_kv, w_uk)
        v = torch.einsum("bkc,chd->bhkd", c_kv, w_uv)
        scores = torch.einsum("bhqd,bhkd->bhqk", q, k) * (D ** -0.5)
        off = Sk - Sq
        qi = torch.arange(Sq)[:, None]
        kj = torch.arange(Sk)[None, :]
        cmask = kj <= (qi + off)
        scores = torch.where(cmask[None, None], scores, -1e9)
        p = _softmax(scores, axis=-1)
        ctx = torch.einsum("bhqk,bhkd->bhqd", p, v)
        return torch.einsum("bhqd,hdm->bqm", ctx, w_o)

    def _B_ref(x, w1, w2):
        h = torch.einsum("bsd,df->bsf", x, w1)
        zero = torch.zeros_like(h)
        h = torch.maximum(h, zero)
        return torch.einsum("bsf,fd->bsd", h, w2)

    x = A_x
    xn = _layernorm(x, axis=-1)
    s = _A_ref(xn, A_c_kv, A_w_q, A_w_uk, A_w_uv, A_w_o)
    g = _silu(_B_ref(xn, B_w1, B_w2))
    return x + s * g
```

```cpp
#include <cuda_runtime.h>
#include <cuda_bf16.h>
#include <cuda.h>
#include <stdint.h>

typedef __nv_bfloat16 bf16;

constexpr int SEQ = 2048;
constexpr int DM  = 512;
constexpr int NH  = 32;
constexpr int HD  = 128;
constexpr int DFF = 1792;

__device__ __align__(1024) bf16 g_xn[SEQ * DM];
__device__ __align__(1024) bf16 g_q[NH * SEQ * HD];
__device__ __align__(1024) bf16 g_k[NH * SEQ * HD];
__device__ __align__(1024) bf16 g_v[NH * SEQ * HD];
__device__ __align__(1024) bf16 g_h[SEQ * DFF];
__device__ __align__(1024) bf16 g_ctx[SEQ * NH * HD];

__device__ __forceinline__ uint32_t smem_u32(const void* p) { return (uint32_t)__cvta_generic_to_shared(p); }

__device__ __forceinline__ void mbar_init(uint32_t bar, uint32_t count) {
  asm volatile("mbarrier.init.shared::cta.b64 [%0], %1;" ::"r"(bar), "r"(count) : "memory");
}
__device__ __forceinline__ void mbar_expect_tx(uint32_t bar, uint32_t bytes) {
  asm volatile("mbarrier.arrive.expect_tx.shared::cta.b64 _, [%0], %1;" ::"r"(bar), "r"(bytes) : "memory");
}
__device__ __forceinline__ void mbar_arrive(uint32_t bar) {
  asm volatile("mbarrier.arrive.shared::cta.b64 _, [%0];" ::"r"(bar) : "memory");
}
__device__ __forceinline__ bool mbar_try_wait(uint32_t bar, uint32_t parity) {
  uint32_t ok;
  asm volatile(
      "{\n.reg .pred p;\n"
      "mbarrier.try_wait.parity.shared::cta.b64 p, [%1], %2;\n"
      "selp.u32 %0, 1, 0, p;\n}"
      : "=r"(ok)
      : "r"(bar), "r"(parity)
      : "memory");
  return ok != 0;
}
__device__ __forceinline__ void mbar_wait(uint32_t bar, uint32_t parity) {
  asm volatile(
      "{\n.reg .pred p;\n.reg .u32 c;\nmov.u32 c, 0;\n"
      "WL_%=:\n"
      "mbarrier.try_wait.parity.shared::cta.b64 p, [%0], %1;\n"
      "@p bra WD_%=;\n"
      "add.u32 c, c, 1;\n"
      "setp.lt.u32 p, c, 4194304;\n"
      "@p bra WL_%=;\n"
      "trap;\n"
      "WD_%=:\n}"
      ::"r"(bar), "r"(parity)
      : "memory");
}
__device__ __forceinline__ void fence_barrier_init() {
  asm volatile("fence.mbarrier_init.release.cluster;" ::: "memory");
}
__device__ __forceinline__ void fence_proxy_async() {
  asm volatile("fence.proxy.async.shared::cta;" ::: "memory");
}
__device__ __forceinline__ void tma_load_2d(uint32_t dst, const CUtensorMap* tm, uint32_t bar, int c0, int c1) {
  asm volatile(
      "cp.async.bulk.tensor.2d.shared::cluster.global.mbarrier::complete_tx::bytes [%0], [%1, {%3, %4}], [%2];"
      ::"r"(dst), "l"(tm), "r"(bar), "r"(c0), "r"(c1)
      : "memory");
}
__device__ __forceinline__ void tma_load_3d(uint32_t dst, const CUtensorMap* tm, uint32_t bar, int c0, int c1, int c2) {
  asm volatile(
      "cp.async.bulk.tensor.3d.shared::cluster.global.mbarrier::complete_tx::bytes [%0], [%1, {%3, %4, %5}], [%2];"
      ::"r"(dst), "l"(tm), "r"(bar), "r"(c0), "r"(c1), "r"(c2)
      : "memory");
}
__device__ __forceinline__ void tma_store_2d(const CUtensorMap* tm, uint32_t src, int c0, int c1) {
  asm volatile("cp.async.bulk.tensor.2d.global.shared::cta.bulk_group [%0, {%2, %3}], [%1];"
               ::"l"(tm), "r"(src), "r"(c0), "r"(c1)
               : "memory");
}
__device__ __forceinline__ void tma_store_commit() { asm volatile("cp.async.bulk.commit_group;" ::: "memory"); }
__device__ __forceinline__ void tma_store_wait_read0() { asm volatile("cp.async.bulk.wait_group.read 0;" ::: "memory"); }
__device__ __forceinline__ void tma_store_wait_all0() { asm volatile("cp.async.bulk.wait_group 0;" ::: "memory"); }
__device__ __forceinline__ void prefetch_tmap(const CUtensorMap* tm) {
  asm volatile("prefetch.tensormap [%0];" ::"l"(tm) : "memory");
}

__device__ __forceinline__ void pdl_wait() { asm volatile("griddepcontrol.wait;" ::: "memory"); }
__device__ __forceinline__ void pdl_launch_dependents() { asm volatile("griddepcontrol.launch_dependents;" ::: "memory"); }

__device__ __forceinline__ void wgmma_fence() { asm volatile("wgmma.fence.sync.aligned;" ::: "memory"); }
__device__ __forceinline__ void wgmma_commit() { asm volatile("wgmma.commit_group.sync.aligned;" ::: "memory"); }
template <int N>
__device__ __forceinline__ void wgmma_wait() {
  asm volatile("wgmma.wait_group.sync.aligned %0;" ::"n"(N) : "memory");
}
template <int R>
__device__ __forceinline__ void reg_fence(float (&d)[R]) {
#pragma unroll
  for (int i = 0; i < R; i++) asm volatile("" : "+f"(d[i])::"memory");
}
template <int R>
__device__ __forceinline__ void reg_fence_u(uint32_t (&d)[R]) {
#pragma unroll
  for (int i = 0; i < R; i++) asm volatile("" : "+r"(d[i])::"memory");
}
template <int R> __device__ __forceinline__ void setmaxnreg_inc() { asm volatile("setmaxnreg.inc.sync.aligned.u32 %0;" ::"n"(R)); }
template <int R> __device__ __forceinline__ void setmaxnreg_dec() { asm volatile("setmaxnreg.dec.sync.aligned.u32 %0;" ::"n"(R)); }

__device__ __forceinline__ void named_bar_sync(int id, int nthreads) {
  asm volatile("bar.sync %0, %1;" ::"r"(id), "r"(nthreads) : "memory");
}
__device__ __forceinline__ void named_bar_arrive(int id, int nthreads) {
  asm volatile("bar.arrive %0, %1;" ::"r"(id), "r"(nthreads) : "memory");
}
__device__ __forceinline__ void stmatrix_x4(uint32_t addr, uint32_t r0, uint32_t r1, uint32_t r2, uint32_t r3) {
  asm volatile("stmatrix.sync.aligned.m8n8.x4.shared.b16 [%0], {%1, %2, %3, %4};" ::"r"(addr), "r"(r0), "r"(r1), "r"(r2),
               "r"(r3)
               : "memory");
}
__device__ __forceinline__ uint32_t pack_bf16(float lo, float hi) {
  uint32_t r;
  asm("cvt.rn.bf16x2.f32 %0, %1, %2;" : "=r"(r) : "f"(hi), "f"(lo));
  return r;
}
__device__ __forceinline__ float ex2_approx(float x) {
  float y;
  asm("ex2.approx.ftz.f32 %0, %1;" : "=f"(y) : "f"(x));
  return y;
}
__device__ __forceinline__ float bf16_round(float x) { return __bfloat162float(__float2bfloat16_rn(x)); }

__device__ __forceinline__ uint64_t make_desc(uint32_t saddr, uint32_t lbo_bytes, uint32_t sbo_bytes) {
  uint64_t d = 0;
  d |= (uint64_t)((saddr & 0x3FFFF) >> 4);
  d |= (uint64_t)((lbo_bytes >> 4) & 0x3FFF) << 16;
  d |= (uint64_t)((sbo_bytes >> 4) & 0x3FFF) << 32;
  d |= (uint64_t)1 << 62;
  return d;
}

template<int TB>
__device__ __forceinline__ void wgmma_m64n128k16_ss(float (&d)[64], uint64_t descA, uint64_t descB, int scaleD) {
  asm volatile("{\n.reg .pred p;\nsetp.ne.b32 p, %66, 0;\n"
    "wgmma.mma_async.sync.aligned.m64n128k16.f32.bf16.bf16 "
    "{%0, %1, %2, %3, %4, %5, %6, %7, %8, %9, %10, %11, %12, %13, %14, %15, %16, %17, %18, %19, %20, %21, %22, %23, %24, %25, %26, %27, %28, %29, %30, %31, %32, %33, %34, %35, %36, %37, %38, %39, %40, %41, %42, %43, %44, %45, %46, %47, %48, %49, %50, %51, %52, %53, %54, %55, %56, %57, %58, %59, %60, %61, %62, %63}, "
    "%64, %65, p, 1, 1, 0, %67;\n}\n"
    : "+f"(d[0]), "+f"(d[1]), "+f"(d[2]), "+f"(d[3]), "+f"(d[4]), "+f"(d[5]), "+f"(d[6]), "+f"(d[7]), "+f"(d[8]), "+f"(d[9]), "+f"(d[10]), "+f"(d[11]), "+f"(d[12]), "+f"(d[13]), "+f"(d[14]), "+f"(d[15]), "+f"(d[16]), "+f"(d[17]), "+f"(d[18]), "+f"(d[19]), "+f"(d[20]), "+f"(d[21]), "+f"(d[22]), "+f"(d[23]), "+f"(d[24]), "+f"(d[25]), "+f"(d[26]), "+f"(d[27]), "+f"(d[28]), "+f"(d[29]), "+f"(d[30]), "+f"(d[31]), "+f"(d[32]), "+f"(d[33]), "+f"(d[34]), "+f"(d[35]), "+f"(d[36]), "+f"(d[37]), "+f"(d[38]), "+f"(d[39]), "+f"(d[40]), "+f"(d[41]), "+f"(d[42]), "+f"(d[43]), "+f"(d[44]), "+f"(d[45]), "+f"(d[46]), "+f"(d[47]), "+f"(d[48]), "+f"(d[49]), "+f"(d[50]), "+f"(d[51]), "+f"(d[52]), "+f"(d[53]), "+f"(d[54]), "+f"(d[55]), "+f"(d[56]), "+f"(d[57]), "+f"(d[58]), "+f"(d[59]), "+f"(d[60]), "+f"(d[61]), "+f"(d[62]), "+f"(d[63])
    : "l"(descA), "l"(descB), "r"(scaleD), "n"(TB));
}

template<int TB>
__device__ __forceinline__ void wgmma_m64n256k16_ss(float (&d)[128], uint64_t descA, uint64_t descB, int scaleD) {
  asm volatile("{\n.reg .pred p;\nsetp.ne.b32 p, %130, 0;\n"
    "wgmma.mma_async.sync.aligned.m64n256k16.f32.bf16.bf16 "
    "{%0, %1, %2, %3, %4, %5, %6, %7, %8, %9, %10, %11, %12, %13, %14, %15, %16, %17, %18, %19, %20, %21, %22, %23, %24, %25, %26, %27, %28, %29, %30, %31, %32, %33, %34, %35, %36, %37, %38, %39, %40, %41, %42, %43, %44, %45, %46, %47, %48, %49, %50, %51, %52, %53, %54, %55, %56, %57, %58, %59, %60, %61, %62, %63, %64, %65, %66, %67, %68, %69, %70, %71, %72, %73, %74, %75, %76, %77, %78, %79, %80, %81, %82, %83, %84, %85, %86, %87, %88, %89, %90, %91, %92, %93, %94, %95, %96, %97, %98, %99, %100, %101, %102, %103, %104, %105, %106, %107, %108, %109, %110, %111, %112, %113, %114, %115, %116, %117, %118, %119, %120, %121, %122, %123, %124, %125, %126, %127}, "
    "%128, %129, p, 1, 1, 0, %131;\n}\n"
    : "+f"(d[0]), "+f"(d[1]), "+f"(d[2]), "+f"(d[3]), "+f"(d[4]), "+f"(d[5]), "+f"(d[6]), "+f"(d[7]), "+f"(d[8]), "+f"(d[9]), "+f"(d[10]), "+f"(d[11]), "+f"(d[12]), "+f"(d[13]), "+f"(d[14]), "+f"(d[15]), "+f"(d[16]), "+f"(d[17]), "+f"(d[18]), "+f"(d[19]), "+f"(d[20]), "+f"(d[21]), "+f"(d[22]), "+f"(d[23]), "+f"(d[24]), "+f"(d[25]), "+f"(d[26]), "+f"(d[27]), "+f"(d[28]), "+f"(d[29]), "+f"(d[30]), "+f"(d[31]), "+f"(d[32]), "+f"(d[33]), "+f"(d[34]), "+f"(d[35]), "+f"(d[36]), "+f"(d[37]), "+f"(d[38]), "+f"(d[39]), "+f"(d[40]), "+f"(d[41]), "+f"(d[42]), "+f"(d[43]), "+f"(d[44]), "+f"(d[45]), "+f"(d[46]), "+f"(d[47]), "+f"(d[48]), "+f"(d[49]), "+f"(d[50]), "+f"(d[51]), "+f"(d[52]), "+f"(d[53]), "+f"(d[54]), "+f"(d[55]), "+f"(d[56]), "+f"(d[57]), "+f"(d[58]), "+f"(d[59]), "+f"(d[60]), "+f"(d[61]), "+f"(d[62]), "+f"(d[63]), "+f"(d[64]), "+f"(d[65]), "+f"(d[66]), "+f"(d[67]), "+f"(d[68]), "+f"(d[69]), "+f"(d[70]), "+f"(d[71]), "+f"(d[72]), "+f"(d[73]), "+f"(d[74]), "+f"(d[75]), "+f"(d[76]), "+f"(d[77]), "+f"(d[78]), "+f"(d[79]), "+f"(d[80]), "+f"(d[81]), "+f"(d[82]), "+f"(d[83]), "+f"(d[84]), "+f"(d[85]), "+f"(d[86]), "+f"(d[87]), "+f"(d[88]), "+f"(d[89]), "+f"(d[90]), "+f"(d[91]), "+f"(d[92]), "+f"(d[93]), "+f"(d[94]), "+f"(d[95]), "+f"(d[96]), "+f"(d[97]), "+f"(d[98]), "+f"(d[99]), "+f"(d[100]), "+f"(d[101]), "+f"(d[102]), "+f"(d[103]), "+f"(d[104]), "+f"(d[105]), "+f"(d[106]), "+f"(d[107]), "+f"(d[108]), "+f"(d[109]), "+f"(d[110]), "+f"(d[111]), "+f"(d[112]), "+f"(d[113]), "+f"(d[114]), "+f"(d[115]), "+f"(d[116]), "+f"(d[117]), "+f"(d[118]), "+f"(d[119]), "+f"(d[120]), "+f"(d[121]), "+f"(d[122]), "+f"(d[123]), "+f"(d[124]), "+f"(d[125]), "+f"(d[126]), "+f"(d[127])
    : "l"(descA), "l"(descB), "r"(scaleD), "n"(TB));
}

template<int TB>
__device__ __forceinline__ void wgmma_m64n128k16_rs(float (&d)[64], uint32_t a0, uint32_t a1, uint32_t a2, uint32_t a3, uint64_t descB, int scaleD) {
  asm volatile("{\n.reg .pred p;\nsetp.ne.b32 p, %69, 0;\n"
    "wgmma.mma_async.sync.aligned.m64n128k16.f32.bf16.bf16 "
    "{%0, %1, %2, %3, %4, %5, %6, %7, %8, %9, %10, %11, %12, %13, %14, %15, %16, %17, %18, %19, %20, %21, %22, %23, %24, %25, %26, %27, %28, %29, %30, %31, %32, %33, %34, %35, %36, %37, %38, %39, %40, %41, %42, %43, %44, %45, %46, %47, %48, %49, %50, %51, %52, %53, %54, %55, %56, %57, %58, %59, %60, %61, %62, %63}, "
    "{%64, %65, %66, %67}, %68, p, 1, 1, %70;\n}\n"
    : "+f"(d[0]), "+f"(d[1]), "+f"(d[2]), "+f"(d[3]), "+f"(d[4]), "+f"(d[5]), "+f"(d[6]), "+f"(d[7]), "+f"(d[8]), "+f"(d[9]), "+f"(d[10]), "+f"(d[11]), "+f"(d[12]), "+f"(d[13]), "+f"(d[14]), "+f"(d[15]), "+f"(d[16]), "+f"(d[17]), "+f"(d[18]), "+f"(d[19]), "+f"(d[20]), "+f"(d[21]), "+f"(d[22]), "+f"(d[23]), "+f"(d[24]), "+f"(d[25]), "+f"(d[26]), "+f"(d[27]), "+f"(d[28]), "+f"(d[29]), "+f"(d[30]), "+f"(d[31]), "+f"(d[32]), "+f"(d[33]), "+f"(d[34]), "+f"(d[35]), "+f"(d[36]), "+f"(d[37]), "+f"(d[38]), "+f"(d[39]), "+f"(d[40]), "+f"(d[41]), "+f"(d[42]), "+f"(d[43]), "+f"(d[44]), "+f"(d[45]), "+f"(d[46]), "+f"(d[47]), "+f"(d[48]), "+f"(d[49]), "+f"(d[50]), "+f"(d[51]), "+f"(d[52]), "+f"(d[53]), "+f"(d[54]), "+f"(d[55]), "+f"(d[56]), "+f"(d[57]), "+f"(d[58]), "+f"(d[59]), "+f"(d[60]), "+f"(d[61]), "+f"(d[62]), "+f"(d[63])
    : "r"(a0), "r"(a1), "r"(a2), "r"(a3), "l"(descB), "r"(scaleD), "n"(TB));
}

__global__ void __launch_bounds__(256) ln_kernel(const bf16* __restrict__ x, bf16* __restrict__ xn) {
  pdl_launch_dependents();
  const int warp = (blockIdx.x * 256 + threadIdx.x) >> 5;
  const int lane = threadIdx.x & 31;
  const uint4* src = reinterpret_cast<const uint4*>(x + (size_t)warp * DM);
  uint4 v0 = src[lane], v1 = src[32 + lane];
  float f[16];
  {
    const __nv_bfloat162* p0 = reinterpret_cast<const __nv_bfloat162*>(&v0);
    const __nv_bfloat162* p1 = reinterpret_cast<const __nv_bfloat162*>(&v1);
#pragma unroll
    for (int i = 0; i < 4; i++) {
      float2 a = __bfloat1622float2(p0[i]);
      f[2 * i] = a.x; f[2 * i + 1] = a.y;
      float2 b = __bfloat1622float2(p1[i]);
      f[8 + 2 * i] = b.x; f[8 + 2 * i + 1] = b.y;
    }
  }
  float sum = 0.f;
#pragma unroll
  for (int i = 0; i < 16; i++) sum += f[i];
#pragma unroll
  for (int o = 16; o > 0; o >>= 1) sum += __shfl_xor_sync(0xffffffffu, sum, o);
  const float mean = sum * (1.0f / DM);
  float sq = 0.f;
#pragma unroll
  for (int i = 0; i < 16; i++) { float d = f[i] - mean; sq += d * d; }
#pragma unroll
  for (int o = 16; o > 0; o >>= 1) sq += __shfl_xor_sync(0xffffffffu, sq, o);
  const float var_b  = bf16_round(sq * (1.0f / DM));
  const float mean_b = bf16_round(mean);
  const float den    = bf16_round(sqrtf(bf16_round(var_b + 1e-5f)));
  uint32_t o[8];
#pragma unroll
  for (int i = 0; i < 8; i++) {
    float a = __fdiv_rn(bf16_round(f[2 * i] - mean_b), den);
    float b = __fdiv_rn(bf16_round(f[2 * i + 1] - mean_b), den);
    o[i] = pack_bf16(a, b);
  }
  uint4* dst = reinterpret_cast<uint4*>(xn + (size_t)warp * DM);
  dst[lane] = make_uint4(o[0], o[1], o[2], o[3]);
  dst[32 + lane] = make_uint4(o[4], o[5], o[6], o[7]);
}

constexpr int G1_STAGES = 4;
constexpr int G1_A_BYTES = 128 * 64 * 2;
constexpr int G1_B_BYTES = 64 * 256 * 2;
constexpr int G1_STAGE_BYTES = G1_A_BYTES + G1_B_BYTES;
constexpr int G1_STG_BYTES = 32768;
constexpr int G1_SMEM = G1_STAGES * G1_STAGE_BYTES + G1_STG_BYTES + 256 + 1024;
constexpr int G1_NTILES_N = 55;
constexpr int G1_TILES = 16 * G1_NTILES_N;

struct G1Maps {
  CUtensorMap a[2];
  CUtensorMap b[4];
  CUtensorMap c[4];
};

__global__ void __launch_bounds__(384, 1) gemm1_kernel(const __grid_constant__ G1Maps maps) {
  extern __shared__ uint8_t smem_raw[];
  const uint32_t base = (smem_u32(smem_raw) + 1023u) & ~1023u;
  const uint32_t stg = base + G1_STAGES * G1_STAGE_BYTES;
  const uint32_t bar_full = stg + G1_STG_BYTES;
  const uint32_t bar_empty = bar_full + 8 * G1_STAGES;
  const int tid = threadIdx.x;
  const int wg = tid >> 7;

  if (tid == 0) {
    for (int s = 0; s < G1_STAGES; s++) {
      mbar_init(bar_full + 8 * s, 1);
      mbar_init(bar_empty + 8 * s, 2);
    }
    fence_barrier_init();
  }
  __syncthreads();
  pdl_launch_dependents();

  if (wg == 0) {
    setmaxnreg_dec<40>();
    if (tid == 0) {
      uint32_t it = 0;
      bool ln_ready = false;
      for (int tile = blockIdx.x; tile < G1_TILES; tile += gridDim.x) {
        const int mt = tile & 15, nt = tile >> 4;
        const int seg = nt >> 4, ntl = nt & 15;
        const CUtensorMap* ma = &maps.a[seg >> 1];
        const CUtensorMap* mb = &maps.b[seg];
        if (seg >= 2 && !ln_ready) { pdl_wait(); ln_ready = true; }
        for (int kb = 0; kb < 8; kb++, it++) {
          const uint32_t s = it % G1_STAGES, ph = (it / G1_STAGES) & 1;
          mbar_wait(bar_empty + 8 * s, ph ^ 1);
          mbar_expect_tx(bar_full + 8 * s, G1_STAGE_BYTES);
          const uint32_t sa = base + s * G1_STAGE_BYTES;
          tma_load_2d(sa, ma, bar_full + 8 * s, kb * 64, mt * 128);
          tma_load_3d(sa + G1_A_BYTES, mb, bar_full + 8 * s, 0, kb * 64, ntl * 4);
        }
      }
    }
  } else {
    setmaxnreg_inc<232>();
    const int cw = wg - 1;
    const int wtid = tid & 127;
    const int warp = wtid >> 5, lane = tid & 31;
    const uint32_t my_stg = stg + cw * 16384;
    float acc[128];
    uint32_t it = 0;
    bool first_store = true;
    for (int tile = blockIdx.x; tile < G1_TILES; tile += gridDim.x) {
      const int mt = tile & 15, nt = tile >> 4;
      const int seg = nt >> 4, ntl = nt & 15;
      for (int kb = 0; kb < 8; kb++, it++) {
        const uint32_t s = it % G1_STAGES, ph = (it / G1_STAGES) & 1;
        mbar_wait(bar_full + 8 * s, ph);
        const uint32_t sa = base + s * G1_STAGE_BYTES;
        const uint64_t da = make_desc(sa + cw * 8192, 16, 1024);
        const uint64_t db = make_desc(sa + G1_A_BYTES, 8192, 1024);
        wgmma_fence();
#pragma unroll
        for (int ks = 0; ks < 4; ks++)
          wgmma_m64n256k16_ss<1>(acc, da + ks * 2, db + ks * 128, (kb | ks) != 0);
        wgmma_commit();
        if (kb > 0) {
          wgmma_wait<1>();
          if (wtid == 0) mbar_arrive(bar_empty + 8 * ((it - 1) % G1_STAGES));
        }
      }
      wgmma_wait<0>();
      reg_fence(acc);
      if (wtid == 0) mbar_arrive(bar_empty + 8 * ((it - 1) % G1_STAGES));

      if (seg == 3) {
#pragma unroll
        for (int i = 0; i < 128; i++) acc[i] = fmaxf(acc[i], 0.f);
      }
      const CUtensorMap* mc = &maps.c[seg];
      const int mi = lane >> 3;
      const int row = warp * 16 + (mi & 1) * 8 + (lane & 7);
#pragma unroll
      for (int pass = 0; pass < 2; pass++) {
        if (!first_store) {
          if (wtid == 0) tma_store_wait_read0();
          named_bar_sync(1 + cw, 128);
        }
        first_store = false;
#pragma unroll
        for (int ch = 0; ch < 2; ch++) {
#pragma unroll
          for (int jj = 0; jj < 4; jj++) {
            const int j = pass * 16 + ch * 8 + jj * 2;
            const uint32_t r0 = pack_bf16(acc[4 * j + 0], acc[4 * j + 1]);
            const uint32_t r1 = pack_bf16(acc[4 * j + 2], acc[4 * j + 3]);
            const uint32_t r2 = pack_bf16(acc[4 * j + 4], acc[4 * j + 5]);
            const uint32_t r3 = pack_bf16(acc[4 * j + 6], acc[4 * j + 7]);
            const int c16 = jj * 2 + (mi >> 1);
            stmatrix_x4(my_stg + ch * 8192 + row * 128 + ((c16 ^ (row & 7)) << 4), r0, r1, r2, r3);
          }
        }
        fence_proxy_async();
        named_bar_sync(1 + cw, 128);
        if (wtid == 0) {
#pragma unroll
          for (int ch = 0; ch < 2; ch++) {
            const int cc = pass * 2 + ch;
            if (seg < 3) {
              const int head = ntl * 2 + (cc >> 1);
              tma_store_2d(mc, my_stg + ch * 8192, (cc & 1) * 64, head * SEQ + mt * 128 + cw * 64);
            } else {
              tma_store_2d(mc, my_stg + ch * 8192, ntl * 256 + cc * 64, mt * 128 + cw * 64);
            }
          }
          tma_store_commit();
        }
      }
    }
    if (wtid == 0) tma_store_wait_all0();
  }
}

constexpr int AT_TILE_BYTES = 128 * 128 * 2;
constexpr int AT_SMEM = 6 * AT_TILE_BYTES + 256 + 1024;
constexpr int AT_ITEMS = NH * 16;
constexpr int AT_MAXPER = 8;

struct AtSched {
  uint16_t item[132 * AT_MAXPER];
};
struct AtMaps {
  CUtensorMap q, k, v;
  CUtensorMap o;
};

__device__ __forceinline__ void attn_softmax(float (&s)[64], float& m0, float& m1, float& l0, float& l1,
                                             float& sc0, float& sc1, const float sl2) {
  float mx0 = fmaxf(s[0], s[1]), mx1 = fmaxf(s[2], s[3]);
#pragma unroll
  for (int j = 1; j < 16; j++) {
    mx0 = fmaxf(mx0, fmaxf(s[4 * j + 0], s[4 * j + 1]));
    mx1 = fmaxf(mx1, fmaxf(s[4 * j + 2], s[4 * j + 3]));
  }
  mx0 = fmaxf(mx0, __shfl_xor_sync(0xffffffffu, mx0, 1));
  mx1 = fmaxf(mx1, __shfl_xor_sync(0xffffffffu, mx1, 1));
  mx0 = fmaxf(mx0, __shfl_xor_sync(0xffffffffu, mx0, 2));
  mx1 = fmaxf(mx1, __shfl_xor_sync(0xffffffffu, mx1, 2));
  const float mn0 = fmaxf(m0, mx0), mn1 = fmaxf(m1, mx1);
  sc0 = ex2_approx((m0 - mn0) * sl2);
  sc1 = ex2_approx((m1 - mn1) * sl2);
  m0 = mn0; m1 = mn1;
  const float ms0 = mn0 * sl2, ms1 = mn1 * sl2;
  float a0 = 0.f, a1 = 0.f;
#pragma unroll
  for (int j = 0; j < 16; j++) {
    s[4 * j + 0] = ex2_approx(fmaf(s[4 * j + 0], sl2, -ms0));
    s[4 * j + 1] = ex2_approx(fmaf(s[4 * j + 1], sl2, -ms0));
    s[4 * j + 2] = ex2_approx(fmaf(s[4 * j + 2], sl2, -ms1));
    s[4 * j + 3] = ex2_approx(fmaf(s[4 * j + 3], sl2, -ms1));
    a0 += s[4 * j + 0] + s[4 * j + 1];
    a1 += s[4 * j + 2] + s[4 * j + 3];
  }
  l0 = l0 * sc0 + a0;
  l1 = l1 * sc1 + a1;
}

constexpr int BAR_EPI0 = 1;
constexpr int BAR_PP0  = 4;

__global__ void __launch_bounds__(384, 1) attn_kernel(const __grid_constant__ AtMaps maps,
                                                      const __grid_constant__ AtSched sched) {
  extern __shared__ uint8_t smem_raw[];
  const uint32_t base = (smem_u32(smem_raw) + 1023u) & ~1023u;
  const uint32_t sQ = base, sK = base + 2 * AT_TILE_BYTES, sV = base + 4 * AT_TILE_BYTES;
  const uint32_t bars = base + 6 * AT_TILE_BYTES;
  const uint32_t q_full = bars, q_empty = bars + 16, k_full = bars + 32, k_empty = bars + 48, v_full = bars + 64,
                 v_empty = bars + 80;
  const int tid = threadIdx.x;
  const int wg = tid >> 7;

  if (tid == 0) {
    for (int s = 0; s < 2; s++) {
      mbar_init(q_full + 8 * s, 1); mbar_init(q_empty + 8 * s, 2);
      mbar_init(k_full + 8 * s, 1); mbar_init(k_empty + 8 * s, 2);
      mbar_init(v_full + 8 * s, 1); mbar_init(v_empty + 8 * s, 2);
    }
    fence_barrier_init();
  }
  __syncthreads();
  pdl_launch_dependents();

  if (wg == 0) {
    setmaxnreg_dec<40>();
    if (tid == 0) {
      prefetch_tmap(&maps.q); prefetch_tmap(&maps.k); prefetch_tmap(&maps.v);
      pdl_wait();
      uint32_t kv_it = 0;
      for (int tl = 0; tl < AT_MAXPER; tl++) {
        const uint32_t item = sched.item[blockIdx.x * AT_MAXPER + tl];
        if (item == 0xFFFFu) break;
        const int h = item >> 4, qi = item & 15;
        const uint32_t qb = tl & 1;
        mbar_wait(q_empty + 8 * qb, ((tl >> 1) & 1) ^ 1);
        mbar_expect_tx(q_full + 8 * qb, AT_TILE_BYTES);
        tma_load_3d(sQ + qb * AT_TILE_BYTES, &maps.q, q_full + 8 * qb, 0, h * SEQ + qi * 128, 0);
        for (int n = qi; n >= 0; n--, kv_it++) {
          const uint32_t st = kv_it & 1, ph = (kv_it >> 1) & 1;
          mbar_wait(k_empty + 8 * st, ph ^ 1);
          mbar_expect_tx(k_full + 8 * st, AT_TILE_BYTES);
          tma_load_3d(sK + st * AT_TILE_BYTES, &maps.k, k_full + 8 * st, 0, h * SEQ + n * 128, 0);
          mbar_wait(v_empty + 8 * st, ph ^ 1);
          mbar_expect_tx(v_full + 8 * st, AT_TILE_BYTES);
          tma_load_3d(sV + st * AT_TILE_BYTES, &maps.v, v_full + 8 * st, 0, h * SEQ + n * 128, 0);
        }
      }
    }
  } else {
    setmaxnreg_inc<232>();
    const int cw = wg - 1;
    const int wtid = tid & 127;
    const int warp = wtid >> 5, lane = tid & 31;
    const float sl2 = 0.08838834764831845f * 1.4426950408889634f;
    const uint64_t dQ0 = make_desc(sQ + cw * 8192, 16, 1024);
    const uint64_t dK0 = make_desc(sK, 16, 1024);
    const uint64_t dV0 = make_desc(sV, 16384, 1024);
    constexpr uint64_t TILE16 = AT_TILE_BYTES >> 4;

    float o[64], s[64];
    uint32_t p[32];
    float m0, m1, l0, l1, sc0, sc1;
    int pend_qb = -1;

    uint32_t item = sched.item[blockIdx.x * AT_MAXPER];
    int tl = 0;
    int h = item >> 4, qi = item & 15, n = qi;
    uint32_t e = 0;
    if (cw == 1) named_bar_arrive(BAR_PP0 + 0, 256);

    const int r0 = cw * 64 + warp * 16 + (lane >> 2);
    const int cq = (lane & 3) * 2;

    mbar_wait(q_full, 0);
    mbar_wait(k_full, 0);
    wgmma_fence();
#pragma unroll
    for (int ks = 0; ks < 8; ks++) {
      const uint64_t off = (uint64_t)(((ks >> 2) * 16384 + (ks & 3) * 32) >> 4);
      wgmma_m64n128k16_ss<0>(s, dQ0 + off, dK0 + off, ks != 0);
    }
    wgmma_commit();
    wgmma_wait<0>();
    reg_fence(s);
    if (wtid == 0) mbar_arrive(k_empty);
#pragma unroll
    for (int j = 0; j < 16; j++) {
      const int c = 8 * j + cq;
      if (c > r0) s[4 * j + 0] = -INFINITY;
      if (c + 1 > r0) s[4 * j + 1] = -INFINITY;
      if (c > r0 + 8) s[4 * j + 2] = -INFINITY;
      if (c + 1 > r0 + 8) s[4 * j + 3] = -INFINITY;
    }
    m0 = -INFINITY; m1 = -INFINITY; l0 = 0.f; l1 = 0.f;
    attn_softmax(s, m0, m1, l0, l1, sc0, sc1, sl2);
    bool first_in_tile = true;

    auto tile_epilogue = [&](float lf0, float lf1, uint32_t qb_, int h_, int qi_) {
      lf0 += __shfl_xor_sync(0xffffffffu, lf0, 1);
      lf1 += __shfl_xor_sync(0xffffffffu, lf1, 1);
      lf0 += __shfl_xor_sync(0xffffffffu, lf0, 2);
      lf1 += __shfl_xor_sync(0xffffffffu, lf1, 2);
      const float il0 = 1.0f / lf0, il1 = 1.0f / lf1;
      const int mi = lane >> 3;
      const int row = warp * 16 + (mi & 1) * 8 + (lane & 7);
      const uint32_t q_s = sQ + qb_ * AT_TILE_BYTES + cw * 8192;
#pragma unroll
      for (int ch = 0; ch < 2; ch++) {
#pragma unroll
        for (int jj = 0; jj < 4; jj++) {
          const int j = ch * 8 + jj * 2;
          const uint32_t a0 = pack_bf16(o[4 * j + 0] * il0, o[4 * j + 1] * il0);
          const uint32_t a1 = pack_bf16(o[4 * j + 2] * il1, o[4 * j + 3] * il1);
          const uint32_t a2 = pack_bf16(o[4 * j + 4] * il0, o[4 * j + 5] * il0);
          const uint32_t a3 = pack_bf16(o[4 * j + 6] * il1, o[4 * j + 7] * il1);
          const int c16 = jj * 2 + (mi >> 1);
          stmatrix_x4(q_s + ch * 16384 + row * 128 + ((c16 ^ (row & 7)) << 4), a0, a1, a2, a3);
        }
      }
      fence_proxy_async();
      named_bar_sync(BAR_EPI0 + cw, 128);
      if (wtid == 0) {
        tma_store_2d(&maps.o, q_s, h_ * 128, qi_ * 128 + cw * 64);
        tma_store_2d(&maps.o, q_s + 16384, h_ * 128 + 64, qi_ * 128 + cw * 64);
        tma_store_commit();
      }
    };

    auto pack_p = [&]() {
#pragma unroll
      for (int i = 0; i < 32; i++) p[i] = pack_bf16(s[2 * i], s[2 * i + 1]);
    };
    auto rescale_o = [&]() {
#pragma unroll
      for (int j = 0; j < 16; j++) {
        o[4 * j + 0] *= sc0; o[4 * j + 1] *= sc0;
        o[4 * j + 2] *= sc1; o[4 * j + 3] *= sc1;
      }
    };
    auto issue_pv = [&](uint32_t stc) {
      const uint64_t dv = dV0 + stc * TILE16;
#pragma unroll
      for (int ks = 0; ks < 8; ks++)
        wgmma_m64n128k16_rs<1>(o, p[4 * ks], p[4 * ks + 1], p[4 * ks + 2], p[4 * ks + 3], dv + (uint64_t)(ks * 128),
                               !(first_in_tile && ks == 0));
      wgmma_commit();
    };

    float lp0 = 0.f, lp1 = 0.f;
    int ph_ = 0, pqi = 0;
    uint32_t pqb = 0;
    bool epi_pending = false;
    uint32_t nitem = (n == 0 && 1 < AT_MAXPER) ? sched.item[blockIdx.x * AT_MAXPER + 1] : 0xFFFFu;
    while (n != 0 || nitem != 0xFFFFu) {
      const bool last_in_tile = (n == 0);
      const uint32_t stc = e & 1, phc = (e >> 1) & 1;
      const uint32_t stn = (e + 1) & 1, phn = ((e + 1) >> 1) & 1;
      const uint32_t qb = tl & 1;
      const uint32_t qbn = last_in_tile ? (qb ^ 1) : qb;

      mbar_wait(k_full + 8 * stn, phn);
      wgmma_wait<0>();
      reg_fence_u(p);
      reg_fence(o);
      if (e > 0 && wtid == 0) mbar_arrive(v_empty + 8 * ((e - 1) & 1));
      if (epi_pending) {
        if (pend_qb >= 0) {
          if (wtid == 0) { tma_store_wait_read0(); mbar_arrive(q_empty + 8 * pend_qb); }
          pend_qb = -1;
        }
        tile_epilogue(lp0, lp1, pqb, ph_, pqi);
        pend_qb = (int)pqb;
        epi_pending = false;
      }
      pack_p();
      if (last_in_tile) {
        if (pend_qb >= 0 && (uint32_t)pend_qb == qbn) {
          if (wtid == 0) { tma_store_wait_read0(); mbar_arrive(q_empty + 8 * pend_qb); }
          pend_qb = -1;
        }
        mbar_wait(q_full + 8 * qbn, ((tl + 1) >> 1) & 1);
      }
      mbar_wait(v_full + 8 * stc, phc);
      named_bar_sync(BAR_PP0 + cw, 256);
      wgmma_fence();
      {
        const uint64_t dq = dQ0 + qbn * TILE16, dk = dK0 + stn * TILE16;
#pragma unroll
        for (int ks = 0; ks < 8; ks++) {
          const uint64_t off = (uint64_t)(((ks >> 2) * 16384 + (ks & 3) * 32) >> 4);
          wgmma_m64n128k16_ss<0>(s, dq + off, dk + off, ks != 0);
        }
        wgmma_commit();
      }
      if (!first_in_tile) rescale_o();
      wgmma_fence();
      issue_pv(stc);
      named_bar_arrive(BAR_PP0 + (cw ^ 1), 256);

      wgmma_wait<1>();
      reg_fence(s);
      if (wtid == 0) {
        mbar_arrive(k_empty + 8 * stn);
        if (pend_qb >= 0) {
          tma_store_wait_read0();
          mbar_arrive(q_empty + 8 * pend_qb);
        }
      }
      pend_qb = -1;
      if (last_in_tile) {
        lp0 = l0; lp1 = l1; ph_ = h; pqi = qi; pqb = qb; epi_pending = true;
#pragma unroll
        for (int j = 0; j < 16; j++) {
          const int c = 8 * j + cq;
          if (c > r0) s[4 * j + 0] = -INFINITY;
          if (c + 1 > r0) s[4 * j + 1] = -INFINITY;
          if (c > r0 + 8) s[4 * j + 2] = -INFINITY;
          if (c + 1 > r0 + 8) s[4 * j + 3] = -INFINITY;
        }
        m0 = -INFINITY; m1 = -INFINITY; l0 = 0.f; l1 = 0.f;
      }
      attn_softmax(s, m0, m1, l0, l1, sc0, sc1, sl2);
      e++;
      first_in_tile = last_in_tile;
      if (last_in_tile) {
        tl++; h = nitem >> 4; qi = nitem & 15; n = qi;
        nitem = 0xFFFFu;
      } else {
        n--;
      }
      if (n == 0 && tl + 1 < AT_MAXPER) nitem = sched.item[blockIdx.x * AT_MAXPER + tl + 1];
    }
    {
      const uint32_t stc = e & 1, phc = (e >> 1) & 1;
      mbar_wait(v_full + 8 * stc, phc);
      wgmma_wait<0>();
      reg_fence_u(p);
      reg_fence(o);
      if (epi_pending) tile_epilogue(lp0, lp1, pqb, ph_, pqi);
      pack_p();
      named_bar_sync(BAR_PP0 + cw, 256);
      if (!first_in_tile) rescale_o();
      wgmma_fence();
      issue_pv(stc);
      named_bar_arrive(BAR_PP0 + (cw ^ 1), 256);
      wgmma_wait<0>();
      reg_fence(o);
      tile_epilogue(l0, l1, (uint32_t)(tl & 1), h, qi);
    }
    if (wtid == 0) tma_store_wait_all0();
  }
}

constexpr int G2_STAGES = 6;
constexpr int G2_A_BYTES = 128 * 64 * 2;
constexpr int G2_B_BYTES = 64 * 128 * 2;
constexpr int G2_STAGE_BYTES = G2_A_BYTES + G2_B_BYTES;
constexpr int G2_SMEM = G2_STAGES * G2_STAGE_BYTES + 256 + 1024;
constexpr int G2_KB_S = 32;
constexpr int G2_KB_F = 14;

struct G2Maps {
  CUtensorMap a_ctx, a_h;
  CUtensorMap b_wo, b_w2;
};

__device__ __forceinline__ void cluster_arrive() { asm volatile("barrier.cluster.arrive.release.aligned;" ::: "memory"); }
__device__ __forceinline__ void cluster_wait() { asm volatile("barrier.cluster.wait.acquire.aligned;" ::: "memory"); }

__global__ void __cluster_dims__(2, 1, 1) __launch_bounds__(384, 1)
gemm2_kernel(const __grid_constant__ G2Maps maps, const bf16* __restrict__ x, bf16* __restrict__ out) {
  extern __shared__ uint8_t smem_raw[];
  const uint32_t base = (smem_u32(smem_raw) + 1023u) & ~1023u;
  const uint32_t bar_full = base + G2_STAGES * G2_STAGE_BYTES;
  const uint32_t bar_empty = bar_full + 8 * G2_STAGES;
  const int tid = threadIdx.x;
  const int wg = tid >> 7;
  const int rank = blockIdx.x & 1;
  const int tile = blockIdx.x >> 1;
  const int mt = tile >> 2, nt = tile & 3;

  if (tid == 0) {
    for (int s = 0; s < G2_STAGES; s++) {
      mbar_init(bar_full + 8 * s, 1);
      mbar_init(bar_empty + 8 * s, 2);
    }
    fence_barrier_init();
  }
  __syncthreads();

  if (wg == 0) {
    setmaxnreg_dec<40>();
    if (tid == 0) {
      prefetch_tmap(&maps.a_ctx); prefetch_tmap(&maps.b_wo); prefetch_tmap(&maps.a_h); prefetch_tmap(&maps.b_w2);
      pdl_wait();
      for (uint32_t it = 0; it < (uint32_t)(G2_KB_S + G2_KB_F); it++) {
        const uint32_t s = it % G2_STAGES, ph = (it / G2_STAGES) & 1;
        mbar_wait(bar_empty + 8 * s, ph ^ 1);
        mbar_expect_tx(bar_full + 8 * s, G2_STAGE_BYTES);
        const uint32_t sa = base + s * G2_STAGE_BYTES;
        if (it < (uint32_t)G2_KB_S) {
          const int k0 = (rank * G2_KB_S + (int)it) * 64;
          tma_load_2d(sa, &maps.a_ctx, bar_full + 8 * s, k0, mt * 128);
          tma_load_3d(sa + G2_A_BYTES, &maps.b_wo, bar_full + 8 * s, 0, k0, nt * 2);
        } else {
          const int k0 = (rank * G2_KB_F + (int)it - G2_KB_S) * 64;
          tma_load_2d(sa, &maps.a_h, bar_full + 8 * s, k0, mt * 128);
          tma_load_3d(sa + G2_A_BYTES, &maps.b_w2, bar_full + 8 * s, 0, k0, nt * 2);
        }
      }
    }
    cluster_arrive(); cluster_wait();
    cluster_arrive(); cluster_wait();
  } else {
    setmaxnreg_inc<232>();
    const int cw = wg - 1;
    const int wtid = tid & 127;
    const int warp = wtid >> 5, lane = tid & 31;
    float acs[64], acf[64];
    uint32_t it = 0;
    for (int kb = 0; kb < G2_KB_S; kb++, it++) {
      const uint32_t s = it % G2_STAGES, ph = (it / G2_STAGES) & 1;
      mbar_wait(bar_full + 8 * s, ph);
      const uint32_t sa = base + s * G2_STAGE_BYTES;
      const uint64_t da = make_desc(sa + cw * 8192, 16, 1024);
      const uint64_t db = make_desc(sa + G2_A_BYTES, 8192, 1024);
      wgmma_fence();
#pragma unroll
      for (int ks = 0; ks < 4; ks++) wgmma_m64n128k16_ss<1>(acs, da + ks * 2, db + ks * 128, (kb | ks) != 0);
      wgmma_commit();
      if (kb > 0) {
        wgmma_wait<1>();
        if (wtid == 0) mbar_arrive(bar_empty + 8 * ((it - 1) % G2_STAGES));
      }
    }
    for (int kb = 0; kb < G2_KB_F; kb++, it++) {
      const uint32_t s = it % G2_STAGES, ph = (it / G2_STAGES) & 1;
      mbar_wait(bar_full + 8 * s, ph);
      const uint32_t sa = base + s * G2_STAGE_BYTES;
      const uint64_t da = make_desc(sa + cw * 8192, 16, 1024);
      const uint64_t db = make_desc(sa + G2_A_BYTES, 8192, 1024);
      wgmma_fence();
#pragma unroll
      for (int ks = 0; ks < 4; ks++) wgmma_m64n128k16_ss<1>(acf, da + ks * 2, db + ks * 128, (kb | ks) != 0);
      wgmma_commit();
      wgmma_wait<1>();
      if (wtid == 0) mbar_arrive(bar_empty + 8 * ((it - 1) % G2_STAGES));
    }
    wgmma_wait<0>();
    reg_fence(acs);
    reg_fence(acf);

    cluster_arrive(); cluster_wait();
    if (cw != rank) {
      uint32_t raddr;
      asm volatile("mapa.shared::cluster.u32 %0, %1, %2;" : "=r"(raddr) : "r"(base), "r"(rank ^ 1));
#pragma unroll
      for (int i = 0; i < 16; i++) {
        asm volatile("st.shared::cluster.v4.f32 [%0], {%1, %2, %3, %4};" ::"r"(raddr + (i * 128 + wtid) * 16),
                     "f"(acs[4 * i]), "f"(acs[4 * i + 1]), "f"(acs[4 * i + 2]), "f"(acs[4 * i + 3])
                     : "memory");
        asm volatile("st.shared::cluster.v4.f32 [%0], {%1, %2, %3, %4};" ::"r"(raddr + 32768 + (i * 128 + wtid) * 16),
                     "f"(acf[4 * i]), "f"(acf[4 * i + 1]), "f"(acf[4 * i + 2]), "f"(acf[4 * i + 3])
                     : "memory");
      }
    }
    cluster_arrive(); cluster_wait();
    if (cw == rank) {
      const int r0 = mt * 128 + cw * 64 + warp * 16 + (lane >> 2);
      const int cq = nt * 128 + (lane & 3) * 2;
#pragma unroll
      for (int i = 0; i < 16; i++) {
        float4 ps, pf;
        asm volatile("ld.shared.v4.f32 {%0, %1, %2, %3}, [%4];" : "=f"(ps.x), "=f"(ps.y), "=f"(ps.z), "=f"(ps.w)
                     : "r"(base + (i * 128 + wtid) * 16));
        asm volatile("ld.shared.v4.f32 {%0, %1, %2, %3}, [%4];" : "=f"(pf.x), "=f"(pf.y), "=f"(pf.z), "=f"(pf.w)
                     : "r"(base + 32768 + (i * 128 + wtid) * 16));
        float sv[4] = {acs[4 * i] + ps.x, acs[4 * i + 1] + ps.y, acs[4 * i + 2] + ps.z, acs[4 * i + 3] + ps.w};
        float fv[4] = {acf[4 * i] + pf.x, acf[4 * i + 1] + pf.y, acf[4 * i + 2] + pf.z, acf[4 * i + 3] + pf.w};
#pragma unroll
        for (int hh = 0; hh < 2; hh++) {
          const size_t off = (size_t)(r0 + hh * 8) * DM + cq + 8 * i;
          const __nv_bfloat162 xv = *reinterpret_cast<const __nv_bfloat162*>(x + off);
          float res[2];
#pragma unroll
          for (int c = 0; c < 2; c++) {
            const float sb = bf16_round(sv[hh * 2 + c]);
            const float fb = bf16_round(fv[hh * 2 + c]);
            const float g = bf16_round(__fdividef(fb, 1.0f + __expf(-fb)));
            const float pr = bf16_round(sb * g);
            res[c] = (c == 0 ? __bfloat162float(xv.x) : __bfloat162float(xv.y)) + pr;
          }
          *reinterpret_cast<uint32_t*>(out + off) = pack_bf16(res[0], res[1]);
        }
      }
    }
  }
}

typedef CUresult (*PFN_encodeTiled)(CUtensorMap*, CUtensorMapDataType, cuuint32_t, void*, const cuuint64_t*,
                                    const cuuint64_t*, const cuuint32_t*, const cuuint32_t*, CUtensorMapInterleave,
                                    CUtensorMapSwizzle, CUtensorMapL2promotion, CUtensorMapFloatOOBfill);

static PFN_encodeTiled get_encode() {
  static PFN_encodeTiled fn = nullptr;
  if (!fn) {
    void* p = nullptr;
    cudaDriverEntryPointQueryResult qr;
    cudaGetDriverEntryPoint("cuTensorMapEncodeTiled", &p, cudaEnableDefault, &qr);
    fn = (PFN_encodeTiled)p;
  }
  return fn;
}

static void make_map_2d(CUtensorMap* m, const void* ptr, uint64_t cols, uint64_t rows, uint32_t bc, uint32_t br) {
  cuuint64_t dims[2] = {cols, rows};
  cuuint64_t strides[1] = {cols * 2};
  cuuint32_t box[2] = {bc, br};
  cuuint32_t es[2] = {1, 1};
  get_encode()(m, CU_TENSOR_MAP_DATA_TYPE_BFLOAT16, 2, const_cast<void*>(ptr), dims, strides, box, es,
               CU_TENSOR_MAP_INTERLEAVE_NONE, CU_TENSOR_MAP_SWIZZLE_128B, CU_TENSOR_MAP_L2_PROMOTION_L2_128B,
               CU_TENSOR_MAP_FLOAT_OOB_FILL_NONE);
}
static void make_map_3d(CUtensorMap* m, const void* ptr, uint64_t cols, uint64_t rows, uint32_t br, uint32_t nchunk) {
  cuuint64_t dims[3] = {64, rows, cols / 64};
  cuuint64_t strides[2] = {cols * 2, 128};
  cuuint32_t box[3] = {64, br, nchunk};
  cuuint32_t es[3] = {1, 1, 1};
  get_encode()(m, CU_TENSOR_MAP_DATA_TYPE_BFLOAT16, 3, const_cast<void*>(ptr), dims, strides, box, es,
               CU_TENSOR_MAP_INTERLEAVE_NONE, CU_TENSOR_MAP_SWIZZLE_128B, CU_TENSOR_MAP_L2_PROMOTION_L2_128B,
               CU_TENSOR_MAP_FLOAT_OOB_FILL_NONE);
}

static void build_attn_schedule(AtSched* sc) {
  int load[132];
  int cnt[132];
  for (int i = 0; i < 132; i++) { load[i] = 0; cnt[i] = 0; }
  for (int i = 0; i < 132 * AT_MAXPER; i++) sc->item[i] = 0xFFFF;
  for (int qi = 15; qi >= 0; qi--) {
    for (int h = 0; h < NH; h++) {
      int best = 0;
      for (int c = 1; c < 132; c++)
        if (load[c] < load[best]) best = c;
      sc->item[best * AT_MAXPER + cnt[best]] = (uint16_t)((h << 4) | qi);
      cnt[best]++;
      load[best] += qi + 1;
    }
  }
}

extern "C" void kernel_launch(void* const* d_in, const int* in_sizes, int n_in, void* d_out, int out_size) {
  const bf16* x = (const bf16*)d_in[0];
  const bf16* ckv = (const bf16*)d_in[1];
  const bf16* wq = (const bf16*)d_in[2];
  const bf16* wuk = (const bf16*)d_in[3];
  const bf16* wuv = (const bf16*)d_in[4];
  const bf16* wo = (const bf16*)d_in[5];
  const bf16* w1 = (const bf16*)d_in[7];
  const bf16* w2 = (const bf16*)d_in[8];
  bf16* out = (bf16*)d_out;

  void *p_xn, *p_q, *p_k, *p_v, *p_h, *p_ctx;
  cudaGetSymbolAddress(&p_xn, g_xn);
  cudaGetSymbolAddress(&p_q, g_q);
  cudaGetSymbolAddress(&p_k, g_k);
  cudaGetSymbolAddress(&p_v, g_v);
  cudaGetSymbolAddress(&p_h, g_h);
  cudaGetSymbolAddress(&p_ctx, g_ctx);

  static bool attr_done = false;
  if (!attr_done) {
    cudaFuncSetAttribute(gemm1_kernel, cudaFuncAttributeMaxDynamicSharedMemorySize, G1_SMEM);
    cudaFuncSetAttribute(attn_kernel, cudaFuncAttributeMaxDynamicSharedMemorySize, AT_SMEM);
    cudaFuncSetAttribute(gemm2_kernel, cudaFuncAttributeMaxDynamicSharedMemorySize, G2_SMEM);
    attr_done = true;
  }

  G1Maps g1;
  make_map_2d(&g1.a[0], ckv, DM, SEQ, 64, 128);
  make_map_2d(&g1.a[1], p_xn, DM, SEQ, 64, 128);
  make_map_3d(&g1.b[0], wuk, NH * HD, DM, 64, 4);
  make_map_3d(&g1.b[1], wuv, NH * HD, DM, 64, 4);
  make_map_3d(&g1.b[2], wq, NH * HD, DM, 64, 4);
  make_map_3d(&g1.b[3], w1, DFF, DM, 64, 4);
  make_map_2d(&g1.c[0], p_k, HD, NH * SEQ, 64, 64);
  make_map_2d(&g1.c[1], p_v, HD, NH * SEQ, 64, 64);
  make_map_2d(&g1.c[2], p_q, HD, NH * SEQ, 64, 64);
  make_map_2d(&g1.c[3], p_h, DFF, SEQ, 64, 64);

  AtMaps am;
  make_map_3d(&am.q, p_q, HD, NH * SEQ, 128, 2);
  make_map_3d(&am.k, p_k, HD, NH * SEQ, 128, 2);
  make_map_3d(&am.v, p_v, HD, NH * SEQ, 128, 2);
  make_map_2d(&am.o, p_ctx, NH * HD, SEQ, 64, 64);
  static AtSched sched;
  static bool sched_done = false;
  if (!sched_done) { build_attn_schedule(&sched); sched_done = true; }

  G2Maps g2;
  make_map_2d(&g2.a_ctx, p_ctx, NH * HD, SEQ, 64, 128);
  make_map_2d(&g2.a_h, p_h, DFF, SEQ, 64, 128);
  make_map_3d(&g2.b_wo, wo, DM, NH * HD, 64, 2);
  make_map_3d(&g2.b_w2, w2, DM, DFF, 64, 2);

  cudaStream_t st = cudaStreamPerThread;
  ln_kernel<<<SEQ / 8, 256, 0, st>>>(x, (bf16*)p_xn);
  {
    cudaLaunchAttribute at[1];
    at[0].id = cudaLaunchAttributeProgrammaticStreamSerialization;
    at[0].val.programmaticStreamSerializationAllowed = 1;
    cudaLaunchConfig_t cfg = {};
    cfg.stream = st; cfg.attrs = at; cfg.numAttrs = 1;
    cfg.gridDim = dim3(132); cfg.blockDim = dim3(384); cfg.dynamicSmemBytes = G1_SMEM;
    cudaLaunchKernelEx(&cfg, gemm1_kernel, g1);
    cfg.gridDim = dim3(132); cfg.blockDim = dim3(384); cfg.dynamicSmemBytes = AT_SMEM;
    cudaLaunchKernelEx(&cfg, attn_kernel, am, sched);
    cfg.gridDim = dim3(128); cfg.blockDim = dim3(384); cfg.dynamicSmemBytes = G2_SMEM;
    cudaLaunchKernelEx(&cfg, gemm2_kernel, g2, x, out);
  }
}
```

```cpp
#include <cuda_runtime.h>
#include <cuda_bf16.h>
#include <cuda.h>
#include <stdint.h>

typedef __nv_bfloat16 bf16;

constexpr int SEQ = 2048;
constexpr int DM  = 512;
constexpr int NH  = 32;
constexpr int HD  = 128;
constexpr int DFF = 1792;

__device__ __align__(1024) bf16 g_xn[SEQ * DM];
__device__ __align__(1024) bf16 g_q[NH * SEQ * HD];
__device__ __align__(1024) bf16 g_k[NH * SEQ * HD];
__device__ __align__(1024) bf16 g_v[NH * SEQ * HD];
__device__ __align__(1024) bf16 g_h[SEQ * DFF];
__device__ __align__(1024) bf16 g_ctx[SEQ * NH * HD];
#define TL(idx)
#define TL2()

__device__ __forceinline__ uint32_t smem_u32(const void* p) { return (uint32_t)__cvta_generic_to_shared(p); }

__device__ __forceinline__ void mbar_init(uint32_t bar, uint32_t count) {
  asm volatile("mbarrier.init.shared::cta.b64 [%0], %1;" ::"r"(bar), "r"(count) : "memory");
}
__device__ __forceinline__ void mbar_expect_tx(uint32_t bar, uint32_t bytes) {
  asm volatile("mbarrier.arrive.expect_tx.shared::cta.b64 _, [%0], %1;" ::"r"(bar), "r"(bytes) : "memory");
}
__device__ __forceinline__ void mbar_arrive(uint32_t bar) {
  asm volatile("mbarrier.arrive.shared::cta.b64 _, [%0];" ::"r"(bar) : "memory");
}
__device__ __forceinline__ bool mbar_try_wait(uint32_t bar, uint32_t parity) {
  uint32_t ok;
  asm volatile(
      "{\n.reg .pred p;\n"
      "mbarrier.try_wait.parity.shared::cta.b64 p, [%1], %2;\n"
      "selp.u32 %0, 1, 0, p;\n}"
      : "=r"(ok)
      : "r"(bar), "r"(parity)
      : "memory");
  return ok != 0;
}
__device__ __forceinline__ void mbar_wait(uint32_t bar, uint32_t parity) {
  asm volatile(
      "{\n.reg .pred p;\n.reg .u32 c;\nmov.u32 c, 0;\n"
      "WL_%=:\n"
      "mbarrier.try_wait.parity.shared::cta.b64 p, [%0], %1;\n"
      "@p bra WD_%=;\n"
      "add.u32 c, c, 1;\n"
      "setp.lt.u32 p, c, 4194304;\n"
      "@p bra WL_%=;\n"
      "trap;\n"
      "WD_%=:\n}"
      ::"r"(bar), "r"(parity)
      : "memory");
}
__device__ __forceinline__ void fence_barrier_init() {
  asm volatile("fence.mbarrier_init.release.cluster;" ::: "memory");
}
__device__ __forceinline__ void fence_proxy_async() {
  asm volatile("fence.proxy.async.shared::cta;" ::: "memory");
}
__device__ __forceinline__ void tma_load_2d(uint32_t dst, const CUtensorMap* tm, uint32_t bar, int c0, int c1) {
  asm volatile(
      "cp.async.bulk.tensor.2d.shared::cluster.global.mbarrier::complete_tx::bytes [%0], [%1, {%3, %4}], [%2];"
      ::"r"(dst), "l"(tm), "r"(bar), "r"(c0), "r"(c1)
      : "memory");
}
__device__ __forceinline__ void tma_load_3d(uint32_t dst, const CUtensorMap* tm, uint32_t bar, int c0, int c1, int c2) {
  asm volatile(
      "cp.async.bulk.tensor.3d.shared::cluster.global.mbarrier::complete_tx::bytes [%0], [%1, {%3, %4, %5}], [%2];"
      ::"r"(dst), "l"(tm), "r"(bar), "r"(c0), "r"(c1), "r"(c2)
      : "memory");
}
__device__ __forceinline__ void tma_load_3d_mc(uint32_t dst, const CUtensorMap* tm, uint32_t bar, int c0, int c1, int c2,
                                               uint16_t mask) {
  asm volatile(
      "cp.async.bulk.tensor.3d.shared::cluster.global.mbarrier::complete_tx::bytes.multicast::cluster"
      " [%0], [%1, {%3, %4, %5}], [%2], %6;"
      ::"r"(dst), "l"(tm), "r"(bar), "r"(c0), "r"(c1), "r"(c2), "h"(mask)
      : "memory");
}
__device__ __forceinline__ void mbar_arrive_cluster(uint32_t bar, uint32_t cta) {
  asm volatile(
      "{\n.reg .b32 ra;\n"
      "mapa.shared::cluster.u32 ra, %0, %1;\n"
      "mbarrier.arrive.relaxed.cluster.shared::cluster.b64 _, [ra];\n}"
      ::"r"(bar), "r"(cta)
      : "memory");
}
__device__ __forceinline__ void cluster_arrive() { asm volatile("barrier.cluster.arrive.release.aligned;" ::: "memory"); }
__device__ __forceinline__ void cluster_wait() { asm volatile("barrier.cluster.wait.acquire.aligned;" ::: "memory"); }
__device__ __forceinline__ void tma_store_2d(const CUtensorMap* tm, uint32_t src, int c0, int c1) {
  asm volatile("cp.async.bulk.tensor.2d.global.shared::cta.bulk_group [%0, {%2, %3}], [%1];"
               ::"l"(tm), "r"(src), "r"(c0), "r"(c1)
               : "memory");
}
__device__ __forceinline__ void tma_store_commit() { asm volatile("cp.async.bulk.commit_group;" ::: "memory"); }
__device__ __forceinline__ void tma_store_wait_read0() { asm volatile("cp.async.bulk.wait_group.read 0;" ::: "memory"); }
__device__ __forceinline__ void tma_store_wait_all0() { asm volatile("cp.async.bulk.wait_group 0;" ::: "memory"); }
__device__ __forceinline__ void prefetch_tmap(const CUtensorMap* tm) {
  asm volatile("prefetch.tensormap [%0];" ::"l"(tm) : "memory");
}

__device__ __forceinline__ void pdl_wait() { asm volatile("griddepcontrol.wait;" ::: "memory"); }
__device__ __forceinline__ void pdl_launch_dependents() { asm volatile("griddepcontrol.launch_dependents;" ::: "memory"); }

__device__ __forceinline__ void wgmma_fence() { asm volatile("wgmma.fence.sync.aligned;" ::: "memory"); }
__device__ __forceinline__ void wgmma_commit() { asm volatile("wgmma.commit_group.sync.aligned;" ::: "memory"); }
template <int N>
__device__ __forceinline__ void wgmma_wait() {
  asm volatile("wgmma.wait_group.sync.aligned %0;" ::"n"(N) : "memory");
}
template <int R>
__device__ __forceinline__ void reg_fence(float (&d)[R]) {
#pragma unroll
  for (int i = 0; i < R; i++) asm volatile("" : "+f"(d[i])::"memory");
}
template <int R>
__device__ __forceinline__ void reg_fence_u(uint32_t (&d)[R]) {
#pragma unroll
  for (int i = 0; i < R; i++) asm volatile("" : "+r"(d[i])::"memory");
}
template <int R> __device__ __forceinline__ void setmaxnreg_inc() { asm volatile("setmaxnreg.inc.sync.aligned.u32 %0;" ::"n"(R)); }
template <int R> __device__ __forceinline__ void setmaxnreg_dec() { asm volatile("setmaxnreg.dec.sync.aligned.u32 %0;" ::"n"(R)); }

__device__ __forceinline__ void named_bar_sync(int id, int nthreads) {
  asm volatile("bar.sync %0, %1;" ::"r"(id), "r"(nthreads) : "memory");
}
__device__ __forceinline__ void named_bar_arrive(int id, int nthreads) {
  asm volatile("bar.arrive %0, %1;" ::"r"(id), "r"(nthreads) : "memory");
}
__device__ __forceinline__ void stmatrix_x4(uint32_t addr, uint32_t r0, uint32_t r1, uint32_t r2, uint32_t r3) {
  asm volatile("stmatrix.sync.aligned.m8n8.x4.shared.b16 [%0], {%1, %2, %3, %4};" ::"r"(addr), "r"(r0), "r"(r1), "r"(r2),
               "r"(r3)
               : "memory");
}
__device__ __forceinline__ uint32_t pack_bf16(float lo, float hi) {
  uint32_t r;
  asm("cvt.rn.bf16x2.f32 %0, %1, %2;" : "=r"(r) : "f"(hi), "f"(lo));
  return r;
}
__device__ __forceinline__ float ex2_approx(float x) {
  float y;
  asm("ex2.approx.ftz.f32 %0, %1;" : "=f"(y) : "f"(x));
  return y;
}
__device__ __forceinline__ float bf16_round(float x) { return __bfloat162float(__float2bfloat16_rn(x)); }

__device__ __forceinline__ uint64_t make_desc(uint32_t saddr, uint32_t lbo_bytes, uint32_t sbo_bytes) {
  uint64_t d = 0;
  d |= (uint64_t)((saddr & 0x3FFFF) >> 4);
  d |= (uint64_t)((lbo_bytes >> 4) & 0x3FFF) << 16;
  d |= (uint64_t)((sbo_bytes >> 4) & 0x3FFF) << 32;
  d |= (uint64_t)1 << 62;
  return d;
}

template<int TB>
__device__ __forceinline__ void wgmma_m64n128k16_ss(float (&d)[64], uint64_t descA, uint64_t descB, int scaleD) {
  asm volatile("{\n.reg .pred p;\nsetp.ne.b32 p, %66, 0;\n"
    "wgmma.mma_async.sync.aligned.m64n128k16.f32.bf16.bf16 "
    "{%0, %1, %2, %3, %4, %5, %6, %7, %8, %9, %10, %11, %12, %13, %14, %15, %16, %17, %18, %19, %20, %21, %22, %23, %24, %25, %26, %27, %28, %29, %30, %31, %32, %33, %34, %35, %36, %37, %38, %39, %40, %41, %42, %43, %44, %45, %46, %47, %48, %49, %50, %51, %52, %53, %54, %55, %56, %57, %58, %59, %60, %61, %62, %63}, "
    "%64, %65, p, 1, 1, 0, %67;\n}\n"
    : "+f"(d[0]), "+f"(d[1]), "+f"(d[2]), "+f"(d[3]), "+f"(d[4]), "+f"(d[5]), "+f"(d[6]), "+f"(d[7]), "+f"(d[8]), "+f"(d[9]), "+f"(d[10]), "+f"(d[11]), "+f"(d[12]), "+f"(d[13]), "+f"(d[14]), "+f"(d[15]), "+f"(d[16]), "+f"(d[17]), "+f"(d[18]), "+f"(d[19]), "+f"(d[20]), "+f"(d[21]), "+f"(d[22]), "+f"(d[23]), "+f"(d[24]), "+f"(d[25]), "+f"(d[26]), "+f"(d[27]), "+f"(d[28]), "+f"(d[29]), "+f"(d[30]), "+f"(d[31]), "+f"(d[32]), "+f"(d[33]), "+f"(d[34]), "+f"(d[35]), "+f"(d[36]), "+f"(d[37]), "+f"(d[38]), "+f"(d[39]), "+f"(d[40]), "+f"(d[41]), "+f"(d[42]), "+f"(d[43]), "+f"(d[44]), "+f"(d[45]), "+f"(d[46]), "+f"(d[47]), "+f"(d[48]), "+f"(d[49]), "+f"(d[50]), "+f"(d[51]), "+f"(d[52]), "+f"(d[53]), "+f"(d[54]), "+f"(d[55]), "+f"(d[56]), "+f"(d[57]), "+f"(d[58]), "+f"(d[59]), "+f"(d[60]), "+f"(d[61]), "+f"(d[62]), "+f"(d[63])
    : "l"(descA), "l"(descB), "r"(scaleD), "n"(TB));
}

template<int TB>
__device__ __forceinline__ void wgmma_m64n256k16_ss(float (&d)[128], uint64_t descA, uint64_t descB, int scaleD) {
  asm volatile("{\n.reg .pred p;\nsetp.ne.b32 p, %130, 0;\n"
    "wgmma.mma_async.sync.aligned.m64n256k16.f32.bf16.bf16 "
    "{%0, %1, %2, %3, %4, %5, %6, %7, %8, %9, %10, %11, %12, %13, %14, %15, %16, %17, %18, %19, %20, %21, %22, %23, %24, %25, %26, %27, %28, %29, %30, %31, %32, %33, %34, %35, %36, %37, %38, %39, %40, %41, %42, %43, %44, %45, %46, %47, %48, %49, %50, %51, %52, %53, %54, %55, %56, %57, %58, %59, %60, %61, %62, %63, %64, %65, %66, %67, %68, %69, %70, %71, %72, %73, %74, %75, %76, %77, %78, %79, %80, %81, %82, %83, %84, %85, %86, %87, %88, %89, %90, %91, %92, %93, %94, %95, %96, %97, %98, %99, %100, %101, %102, %103, %104, %105, %106, %107, %108, %109, %110, %111, %112, %113, %114, %115, %116, %117, %118, %119, %120, %121, %122, %123, %124, %125, %126, %127}, "
    "%128, %129, p, 1, 1, 0, %131;\n}\n"
    : "+f"(d[0]), "+f"(d[1]), "+f"(d[2]), "+f"(d[3]), "+f"(d[4]), "+f"(d[5]), "+f"(d[6]), "+f"(d[7]), "+f"(d[8]), "+f"(d[9]), "+f"(d[10]), "+f"(d[11]), "+f"(d[12]), "+f"(d[13]), "+f"(d[14]), "+f"(d[15]), "+f"(d[16]), "+f"(d[17]), "+f"(d[18]), "+f"(d[19]), "+f"(d[20]), "+f"(d[21]), "+f"(d[22]), "+f"(d[23]), "+f"(d[24]), "+f"(d[25]), "+f"(d[26]), "+f"(d[27]), "+f"(d[28]), "+f"(d[29]), "+f"(d[30]), "+f"(d[31]), "+f"(d[32]), "+f"(d[33]), "+f"(d[34]), "+f"(d[35]), "+f"(d[36]), "+f"(d[37]), "+f"(d[38]), "+f"(d[39]), "+f"(d[40]), "+f"(d[41]), "+f"(d[42]), "+f"(d[43]), "+f"(d[44]), "+f"(d[45]), "+f"(d[46]), "+f"(d[47]), "+f"(d[48]), "+f"(d[49]), "+f"(d[50]), "+f"(d[51]), "+f"(d[52]), "+f"(d[53]), "+f"(d[54]), "+f"(d[55]), "+f"(d[56]), "+f"(d[57]), "+f"(d[58]), "+f"(d[59]), "+f"(d[60]), "+f"(d[61]), "+f"(d[62]), "+f"(d[63]), "+f"(d[64]), "+f"(d[65]), "+f"(d[66]), "+f"(d[67]), "+f"(d[68]), "+f"(d[69]), "+f"(d[70]), "+f"(d[71]), "+f"(d[72]), "+f"(d[73]), "+f"(d[74]), "+f"(d[75]), "+f"(d[76]), "+f"(d[77]), "+f"(d[78]), "+f"(d[79]), "+f"(d[80]), "+f"(d[81]), "+f"(d[82]), "+f"(d[83]), "+f"(d[84]), "+f"(d[85]), "+f"(d[86]), "+f"(d[87]), "+f"(d[88]), "+f"(d[89]), "+f"(d[90]), "+f"(d[91]), "+f"(d[92]), "+f"(d[93]), "+f"(d[94]), "+f"(d[95]), "+f"(d[96]), "+f"(d[97]), "+f"(d[98]), "+f"(d[99]), "+f"(d[100]), "+f"(d[101]), "+f"(d[102]), "+f"(d[103]), "+f"(d[104]), "+f"(d[105]), "+f"(d[106]), "+f"(d[107]), "+f"(d[108]), "+f"(d[109]), "+f"(d[110]), "+f"(d[111]), "+f"(d[112]), "+f"(d[113]), "+f"(d[114]), "+f"(d[115]), "+f"(d[116]), "+f"(d[117]), "+f"(d[118]), "+f"(d[119]), "+f"(d[120]), "+f"(d[121]), "+f"(d[122]), "+f"(d[123]), "+f"(d[124]), "+f"(d[125]), "+f"(d[126]), "+f"(d[127])
    : "l"(descA), "l"(descB), "r"(scaleD), "n"(TB));
}

template<int TB>
__device__ __forceinline__ void wgmma_m64n128k16_rs(float (&d)[64], uint32_t a0, uint32_t a1, uint32_t a2, uint32_t a3, uint64_t descB, int scaleD) {
  asm volatile("{\n.reg .pred p;\nsetp.ne.b32 p, %69, 0;\n"
    "wgmma.mma_async.sync.aligned.m64n128k16.f32.bf16.bf16 "
    "{%0, %1, %2, %3, %4, %5, %6, %7, %8, %9, %10, %11, %12, %13, %14, %15, %16, %17, %18, %19, %20, %21, %22, %23, %24, %25, %26, %27, %28, %29, %30, %31, %32, %33, %34, %35, %36, %37, %38, %39, %40, %41, %42, %43, %44, %45, %46, %47, %48, %49, %50, %51, %52, %53, %54, %55, %56, %57, %58, %59, %60, %61, %62, %63}, "
    "{%64, %65, %66, %67}, %68, p, 1, 1, %70;\n}\n"
    : "+f"(d[0]), "+f"(d[1]), "+f"(d[2]), "+f"(d[3]), "+f"(d[4]), "+f"(d[5]), "+f"(d[6]), "+f"(d[7]), "+f"(d[8]), "+f"(d[9]), "+f"(d[10]), "+f"(d[11]), "+f"(d[12]), "+f"(d[13]), "+f"(d[14]), "+f"(d[15]), "+f"(d[16]), "+f"(d[17]), "+f"(d[18]), "+f"(d[19]), "+f"(d[20]), "+f"(d[21]), "+f"(d[22]), "+f"(d[23]), "+f"(d[24]), "+f"(d[25]), "+f"(d[26]), "+f"(d[27]), "+f"(d[28]), "+f"(d[29]), "+f"(d[30]), "+f"(d[31]), "+f"(d[32]), "+f"(d[33]), "+f"(d[34]), "+f"(d[35]), "+f"(d[36]), "+f"(d[37]), "+f"(d[38]), "+f"(d[39]), "+f"(d[40]), "+f"(d[41]), "+f"(d[42]), "+f"(d[43]), "+f"(d[44]), "+f"(d[45]), "+f"(d[46]), "+f"(d[47]), "+f"(d[48]), "+f"(d[49]), "+f"(d[50]), "+f"(d[51]), "+f"(d[52]), "+f"(d[53]), "+f"(d[54]), "+f"(d[55]), "+f"(d[56]), "+f"(d[57]), "+f"(d[58]), "+f"(d[59]), "+f"(d[60]), "+f"(d[61]), "+f"(d[62]), "+f"(d[63])
    : "r"(a0), "r"(a1), "r"(a2), "r"(a3), "l"(descB), "r"(scaleD), "n"(TB));
}

__global__ void __launch_bounds__(256) ln_kernel(const bf16* __restrict__ x, bf16* __restrict__ xn) {
  pdl_launch_dependents();
  const int warp = (blockIdx.x * 256 + threadIdx.x) >> 5;
  const int lane = threadIdx.x & 31;
  const uint4* src = reinterpret_cast<const uint4*>(x + (size_t)warp * DM);
  uint4 v0 = src[lane], v1 = src[32 + lane];
  float f[16];
  {
    const __nv_bfloat162* p0 = reinterpret_cast<const __nv_bfloat162*>(&v0);
    const __nv_bfloat162* p1 = reinterpret_cast<const __nv_bfloat162*>(&v1);
#pragma unroll
    for (int i = 0; i < 4; i++) {
      float2 a = __bfloat1622float2(p0[i]);
      f[2 * i] = a.x; f[2 * i + 1] = a.y;
      float2 b = __bfloat1622float2(p1[i]);
      f[8 + 2 * i] = b.x; f[8 + 2 * i + 1] = b.y;
    }
  }
  float sum = 0.f;
#pragma unroll
  for (int i = 0; i < 16; i++) sum += f[i];
#pragma unroll
  for (int o = 16; o > 0; o >>= 1) sum += __shfl_xor_sync(0xffffffffu, sum, o);
  const float mean = sum * (1.0f / DM);
  float sq = 0.f;
#pragma unroll
  for (int i = 0; i < 16; i++) { float d = f[i] - mean; sq += d * d; }
#pragma unroll
  for (int o = 16; o > 0; o >>= 1) sq += __shfl_xor_sync(0xffffffffu, sq, o);
  const float var_b  = bf16_round(sq * (1.0f / DM));
  const float mean_b = bf16_round(mean);
  const float den    = bf16_round(sqrtf(bf16_round(var_b + 1e-5f)));
  uint32_t o[8];
#pragma unroll
  for (int i = 0; i < 8; i++) {
    float a = __fdiv_rn(bf16_round(f[2 * i] - mean_b), den);
    float b = __fdiv_rn(bf16_round(f[2 * i + 1] - mean_b), den);
    o[i] = pack_bf16(a, b);
  }
  uint4* dst = reinterpret_cast<uint4*>(xn + (size_t)warp * DM);
  dst[lane] = make_uint4(o[0], o[1], o[2], o[3]);
  dst[32 + lane] = make_uint4(o[4], o[5], o[6], o[7]);
}

constexpr int G1_STAGES = 4;
constexpr int G1_A_BYTES = 128 * 64 * 2;
constexpr int G1_B_BYTES = 64 * 256 * 2;
constexpr int G1_STAGE_BYTES = G1_A_BYTES + G1_B_BYTES;
constexpr int G1_STG_BYTES = 32768;
constexpr int G1_SMEM = G1_STAGES * G1_STAGE_BYTES + G1_STG_BYTES + 256 + 1024;
constexpr int G1_NTILES_N = 55;
constexpr int G1_TILES = 16 * G1_NTILES_N;

struct G1Maps {
  CUtensorMap a[2];
  CUtensorMap b[4];
  CUtensorMap c[4];
};

__global__ void __cluster_dims__(2, 1, 1) __launch_bounds__(384, 1)
gemm1_kernel(const __grid_constant__ G1Maps maps) {
  extern __shared__ uint8_t smem_raw[];
  const uint32_t base = (smem_u32(smem_raw) + 1023u) & ~1023u;
  const uint32_t stg = base + G1_STAGES * G1_STAGE_BYTES;
  const uint32_t bar_full = stg + G1_STG_BYTES;
  const uint32_t bar_empty = bar_full + 8 * G1_STAGES;
  const int tid = threadIdx.x;
  const int wg = tid >> 7;
  const int rank = blockIdx.x & 1;
  const int cid = blockIdx.x >> 1;
  const int nclusters = gridDim.x >> 1;

  if (tid == 0) {
    for (int s = 0; s < G1_STAGES; s++) {
      mbar_init(bar_full + 8 * s, 1);
      mbar_init(bar_empty + 8 * s, 4);
    }
    fence_barrier_init();
  }
  __syncthreads();
  cluster_arrive(); cluster_wait();
  pdl_launch_dependents();

  if (wg == 0) {
    setmaxnreg_dec<40>();
    if (tid == 0) {
      uint32_t it = 0;
      bool ln_ready = false;
      for (int ct = cid; ct < G1_TILES / 2; ct += nclusters) {
        const int mt = (ct & 7) * 2 + rank, nt = ct >> 3;
        const int seg = nt >> 4, ntl = nt & 15;
        const CUtensorMap* ma = &maps.a[seg >> 1];
        const CUtensorMap* mb = &maps.b[seg];
        if (seg >= 2 && !ln_ready) { pdl_wait(); ln_ready = true; }
        for (int kb = 0; kb < 8; kb++, it++) {
          const uint32_t s = it % G1_STAGES, ph = (it / G1_STAGES) & 1;
          mbar_wait(bar_empty + 8 * s, ph ^ 1);
          mbar_expect_tx(bar_full + 8 * s, G1_STAGE_BYTES);
          const uint32_t sa = base + s * G1_STAGE_BYTES;
          tma_load_2d(sa, ma, bar_full + 8 * s, kb * 64, mt * 128);
          tma_load_3d_mc(sa + G1_A_BYTES + rank * (G1_B_BYTES / 2), mb, bar_full + 8 * s, 0, kb * 64,
                         ntl * 4 + rank * 2, (uint16_t)3);
        }
      }
    }
  } else {
    setmaxnreg_inc<232>();
    const int cw = wg - 1;
    const int wtid = tid & 127;
    const int warp = wtid >> 5, lane = tid & 31;
    const uint32_t my_stg = stg + cw * 16384;
    float acc[128];
    uint32_t pk[64];
    uint32_t it = 0;
    bool pending = false, stored_before = false;
    int p_seg = 0, p_ntl = 0, p_mt = 0;
    int tlc = 0; (void)tlc;
    const int mi = lane >> 3;
    const int row = warp * 16 + (mi & 1) * 8 + (lane & 7);

    const uint32_t w_stg = my_stg + warp * 4096;
    const int lrow = (mi & 1) * 8 + (lane & 7);
    auto flush_chunk = [&](int cc) {
      if (stored_before) {
        if (lane == 0) asm volatile("cp.async.bulk.wait_group.read 1;" ::: "memory");
        __syncwarp();
      }
      const uint32_t buf = w_stg + (cc & 1) * 2048;
#pragma unroll
      for (int jj = 0; jj < 4; jj++) {
        const int q = cc * 16 + jj * 4;
        const int c16 = jj * 2 + (mi >> 1);
        stmatrix_x4(buf + lrow * 128 + ((c16 ^ (lrow & 7)) << 4), pk[q], pk[q + 1], pk[q + 2], pk[q + 3]);
      }
      fence_proxy_async();
      __syncwarp();
      if (lane == 0) {
        const CUtensorMap* mc = &maps.c[p_seg];
        const int r0 = p_mt * 128 + cw * 64 + warp * 16;
        if (p_seg < 3) tma_store_2d(mc, buf, (cc & 1) * 64, (p_ntl * 2 + (cc >> 1)) * SEQ + r0);
        else           tma_store_2d(mc, buf, p_ntl * 256 + cc * 64, r0);
        tma_store_commit();
      }
      if (cc >= 1) stored_before = true;
    };

    for (int ct = cid; ct < G1_TILES / 2; ct += nclusters) {
      const int mt = (ct & 7) * 2 + rank, nt = ct >> 3;
      const int seg = nt >> 4, ntl = nt & 15;
      TL(0);
      for (int kb = 0; kb < 8; kb++, it++) {
        const uint32_t s = it % G1_STAGES, ph = (it / G1_STAGES) & 1;
        mbar_wait(bar_full + 8 * s, ph);
        if (kb == 0) TL(1);
        const uint32_t sa = base + s * G1_STAGE_BYTES;
        const uint64_t da = make_desc(sa + cw * 8192, 16, 1024);
        const uint64_t db = make_desc(sa + G1_A_BYTES, 8192, 1024);
        wgmma_fence();
#pragma unroll
        for (int ks = 0; ks < 4; ks++)
          wgmma_m64n256k16_ss<1>(acc, da + ks * 2, db + ks * 128, (kb | ks) != 0);
        wgmma_commit();
        if (pending && kb >= 1 && kb <= 4) {
          if (kb == 1) flush_chunk(0);
          else if (kb == 2) flush_chunk(1);
          else if (kb == 3) flush_chunk(2);
          else { flush_chunk(3); pending = false; }
        }
        if (kb > 0) {
          wgmma_wait<1>();
          if (wtid == 0) {
            const uint32_t eb = bar_empty + 8 * ((it - 1) % G1_STAGES);
            mbar_arrive(eb);
            mbar_arrive_cluster(eb, rank ^ 1);
          }
        }
      }
      wgmma_wait<0>();
      reg_fence(acc);
      TL(2);
      if (wtid == 0) {
        const uint32_t eb = bar_empty + 8 * ((it - 1) % G1_STAGES);
        mbar_arrive(eb);
        mbar_arrive_cluster(eb, rank ^ 1);
      }
      if (seg == 3) {
#pragma unroll
        for (int i = 0; i < 64; i++) pk[i] = pack_bf16(fmaxf(acc[2 * i], 0.f), fmaxf(acc[2 * i + 1], 0.f));
      } else {
#pragma unroll
        for (int i = 0; i < 64; i++) pk[i] = pack_bf16(acc[2 * i], acc[2 * i + 1]);
      }
      pending = true; p_seg = seg; p_ntl = ntl; p_mt = mt;
    }
    if (pending) { flush_chunk(0); flush_chunk(1); flush_chunk(2); flush_chunk(3); }
    if (lane == 0) tma_store_wait_all0();
  }
  cluster_arrive(); cluster_wait();
}

constexpr int AT_TILE_BYTES = 128 * 128 * 2;
constexpr int AT_SMEM = 6 * AT_TILE_BYTES + 256 + 1024;
constexpr int AT_ITEMS = NH * 16;
constexpr int AT_MAXPER = 8;

struct AtSched {
  uint16_t item[132 * AT_MAXPER];
};
struct AtMaps {
  CUtensorMap q, k, v;
  CUtensorMap o;
};

__device__ __forceinline__ void attn_softmax(float (&s)[64], float& m0, float& m1, float& l0, float& l1,
                                             float& sc0, float& sc1, const float sl2) {
  float mx0 = fmaxf(s[0], s[1]), mx1 = fmaxf(s[2], s[3]);
#pragma unroll
  for (int j = 1; j < 16; j++) {
    mx0 = fmaxf(mx0, fmaxf(s[4 * j + 0], s[4 * j + 1]));
    mx1 = fmaxf(mx1, fmaxf(s[4 * j + 2], s[4 * j + 3]));
  }
  mx0 = fmaxf(mx0, __shfl_xor_sync(0xffffffffu, mx0, 1));
  mx1 = fmaxf(mx1, __shfl_xor_sync(0xffffffffu, mx1, 1));
  mx0 = fmaxf(mx0, __shfl_xor_sync(0xffffffffu, mx0, 2));
  mx1 = fmaxf(mx1, __shfl_xor_sync(0xffffffffu, mx1, 2));
  const float mn0 = fmaxf(m0, mx0), mn1 = fmaxf(m1, mx1);
  sc0 = ex2_approx((m0 - mn0) * sl2);
  sc1 = ex2_approx((m1 - mn1) * sl2);
  m0 = mn0; m1 = mn1;
  const float ms0 = mn0 * sl2, ms1 = mn1 * sl2;
  float a0 = 0.f, a1 = 0.f;
#pragma unroll
  for (int j = 0; j < 16; j++) {
    s[4 * j + 0] = ex2_approx(fmaf(s[4 * j + 0], sl2, -ms0));
    s[4 * j + 1] = ex2_approx(fmaf(s[4 * j + 1], sl2, -ms0));
    s[4 * j + 2] = ex2_approx(fmaf(s[4 * j + 2], sl2, -ms1));
    s[4 * j + 3] = ex2_approx(fmaf(s[4 * j + 3], sl2, -ms1));
    a0 += s[4 * j + 0] + s[4 * j + 1];
    a1 += s[4 * j + 2] + s[4 * j + 3];
  }
  l0 = l0 * sc0 + a0;
  l1 = l1 * sc1 + a1;
}

constexpr int BAR_EPI0 = 1;
constexpr int BAR_PP0  = 4;

__global__ void __launch_bounds__(384, 1) attn_kernel(const __grid_constant__ AtMaps maps,
                                                      const __grid_constant__ AtSched sched) {
  extern __shared__ uint8_t smem_raw[];
  const uint32_t base = (smem_u32(smem_raw) + 1023u) & ~1023u;
  const uint32_t sQ = base, sK = base + 2 * AT_TILE_BYTES, sV = base + 4 * AT_TILE_BYTES;
  const uint32_t bars = base + 6 * AT_TILE_BYTES;
  const uint32_t q_full = bars, q_empty = bars + 16, k_full = bars + 32, k_empty = bars + 48, v_full = bars + 64,
                 v_empty = bars + 80;
  const int tid = threadIdx.x;
  const int wg = tid >> 7;

  if (tid == 0) {
    for (int s = 0; s < 2; s++) {
      mbar_init(q_full + 8 * s, 1); mbar_init(q_empty + 8 * s, 2);
      mbar_init(k_full + 8 * s, 1); mbar_init(k_empty + 8 * s, 2);
      mbar_init(v_full + 8 * s, 1); mbar_init(v_empty + 8 * s, 2);
    }
    fence_barrier_init();
  }
  __syncthreads();
  pdl_launch_dependents();

  if (wg == 0) {
    setmaxnreg_dec<40>();
    if (tid == 0) {
      prefetch_tmap(&maps.q); prefetch_tmap(&maps.k); prefetch_tmap(&maps.v);
      pdl_wait();
      uint32_t kv_it = 0;
      for (int tl = 0; tl < AT_MAXPER; tl++) {
        const uint32_t item = sched.item[blockIdx.x * AT_MAXPER + tl];
        if (item == 0xFFFFu) break;
        const int h = item >> 4, qi = item & 15;
        const uint32_t qb = tl & 1;
        mbar_wait(q_empty + 8 * qb, ((tl >> 1) & 1) ^ 1);
        mbar_expect_tx(q_full + 8 * qb, AT_TILE_BYTES);
        tma_load_3d(sQ + qb * AT_TILE_BYTES, &maps.q, q_full + 8 * qb, 0, h * SEQ + qi * 128, 0);
        for (int n = qi; n >= 0; n--, kv_it++) {
          const uint32_t st = kv_it & 1, ph = (kv_it >> 1) & 1;
          mbar_wait(k_empty + 8 * st, ph ^ 1);
          mbar_expect_tx(k_full + 8 * st, AT_TILE_BYTES);
          tma_load_3d(sK + st * AT_TILE_BYTES, &maps.k, k_full + 8 * st, 0, h * SEQ + n * 128, 0);
          mbar_wait(v_empty + 8 * st, ph ^ 1);
          mbar_expect_tx(v_full + 8 * st, AT_TILE_BYTES);
          tma_load_3d(sV + st * AT_TILE_BYTES, &maps.v, v_full + 8 * st, 0, h * SEQ + n * 128, 0);
        }
      }
    }
  } else {
    setmaxnreg_inc<232>();
    const int cw = wg - 1;
    const int wtid = tid & 127;
    const int warp = wtid >> 5, lane = tid & 31;
    const float sl2 = 0.08838834764831845f * 1.4426950408889634f;
    const uint64_t dQ0 = make_desc(sQ + cw * 8192, 16, 1024);
    const uint64_t dK0 = make_desc(sK, 16, 1024);
    const uint64_t dV0 = make_desc(sV, 16384, 1024);
    constexpr uint64_t TILE16 = AT_TILE_BYTES >> 4;

    float o[64], s[64];
    uint32_t p[32];
    float m0, m1, l0, l1, sc0, sc1;
    int pend_qb = -1;

    uint32_t item = sched.item[blockIdx.x * AT_MAXPER];
    int tl = 0;
    int h = item >> 4, qi = item & 15, n = qi;
    uint32_t e = 0;
    if (cw == 1) named_bar_arrive(BAR_PP0 + 0, 256);

    const int r0 = cw * 64 + warp * 16 + (lane >> 2);
    const int cq = (lane & 3) * 2;

    mbar_wait(q_full, 0);
    mbar_wait(k_full, 0);
    wgmma_fence();
#pragma unroll
    for (int ks = 0; ks < 8; ks++) {
      const uint64_t off = (uint64_t)(((ks >> 2) * 16384 + (ks & 3) * 32) >> 4);
      wgmma_m64n128k16_ss<0>(s, dQ0 + off, dK0 + off, ks != 0);
    }
    wgmma_commit();
    wgmma_wait<0>();
    reg_fence(s);
    if (wtid == 0) mbar_arrive(k_empty);
#pragma unroll
    for (int j = 0; j < 16; j++) {
      const int c = 8 * j + cq;
      if (c > r0) s[4 * j + 0] = -INFINITY;
      if (c + 1 > r0) s[4 * j + 1] = -INFINITY;
      if (c > r0 + 8) s[4 * j + 2] = -INFINITY;
      if (c + 1 > r0 + 8) s[4 * j + 3] = -INFINITY;
    }
    m0 = -INFINITY; m1 = -INFINITY; l0 = 0.f; l1 = 0.f;
    attn_softmax(s, m0, m1, l0, l1, sc0, sc1, sl2);
    bool first_in_tile = true;

    auto tile_epilogue = [&](float lf0, float lf1, uint32_t qb_, int h_, int qi_) {
      lf0 += __shfl_xor_sync(0xffffffffu, lf0, 1);
      lf1 += __shfl_xor_sync(0xffffffffu, lf1, 1);
      lf0 += __shfl_xor_sync(0xffffffffu, lf0, 2);
      lf1 += __shfl_xor_sync(0xffffffffu, lf1, 2);
      const float il0 = 1.0f / lf0, il1 = 1.0f / lf1;
      const int mi = lane >> 3;
      const int row = warp * 16 + (mi & 1) * 8 + (lane & 7);
      const uint32_t q_s = sQ + qb_ * AT_TILE_BYTES + cw * 8192;
#pragma unroll
      for (int ch = 0; ch < 2; ch++) {
#pragma unroll
        for (int jj = 0; jj < 4; jj++) {
          const int j = ch * 8 + jj * 2;
          const uint32_t a0 = pack_bf16(o[4 * j + 0] * il0, o[4 * j + 1] * il0);
          const uint32_t a1 = pack_bf16(o[4 * j + 2] * il1, o[4 * j + 3] * il1);
          const uint32_t a2 = pack_bf16(o[4 * j + 4] * il0, o[4 * j + 5] * il0);
          const uint32_t a3 = pack_bf16(o[4 * j + 6] * il1, o[4 * j + 7] * il1);
          const int c16 = jj * 2 + (mi >> 1);
          stmatrix_x4(q_s + ch * 16384 + row * 128 + ((c16 ^ (row & 7)) << 4), a0, a1, a2, a3);
        }
      }
      fence_proxy_async();
      named_bar_sync(BAR_EPI0 + cw, 128);
      if (wtid == 0) {
        tma_store_2d(&maps.o, q_s, h_ * 128, qi_ * 128 + cw * 64);
        tma_store_2d(&maps.o, q_s + 16384, h_ * 128 + 64, qi_ * 128 + cw * 64);
        tma_store_commit();
      }
    };

    auto pack_p = [&]() {
#pragma unroll
      for (int i = 0; i < 32; i++) p[i] = pack_bf16(s[2 * i], s[2 * i + 1]);
    };
    auto rescale_o = [&]() {
#pragma unroll
      for (int j = 0; j < 16; j++) {
        o[4 * j + 0] *= sc0; o[4 * j + 1] *= sc0;
        o[4 * j + 2] *= sc1; o[4 * j + 3] *= sc1;
      }
    };
    auto issue_pv = [&](uint32_t stc) {
      const uint64_t dv = dV0 + stc * TILE16;
#pragma unroll
      for (int ks = 0; ks < 8; ks++)
        wgmma_m64n128k16_rs<1>(o, p[4 * ks], p[4 * ks + 1], p[4 * ks + 2], p[4 * ks + 3], dv + (uint64_t)(ks * 128),
                               !(first_in_tile && ks == 0));
      wgmma_commit();
    };

    int tl2c = 0; (void)tl2c;
    float lp0 = 0.f, lp1 = 0.f;
    int ph_ = 0, pqi = 0;
    uint32_t pqb = 0;
    bool epi_pending = false;
    uint32_t nitem = (n == 0 && 1 < AT_MAXPER) ? sched.item[blockIdx.x * AT_MAXPER + 1] : 0xFFFFu;
    while (n != 0 || nitem != 0xFFFFu) {
      const bool last_in_tile = (n == 0);
      const uint32_t stc = e & 1, phc = (e >> 1) & 1;
      const uint32_t stn = (e + 1) & 1, phn = ((e + 1) >> 1) & 1;
      const uint32_t qb = tl & 1;
      const uint32_t qbn = last_in_tile ? (qb ^ 1) : qb;

      mbar_wait(k_full + 8 * stn, phn);
      wgmma_wait<0>();
      reg_fence_u(p);
      reg_fence(o);
      if (e > 0 && wtid == 0) mbar_arrive(v_empty + 8 * ((e - 1) & 1));
      if (epi_pending) {
        if (pend_qb >= 0) {
          if (wtid == 0) { tma_store_wait_read0(); mbar_arrive(q_empty + 8 * pend_qb); }
          pend_qb = -1;
        }
        tile_epilogue(lp0, lp1, pqb, ph_, pqi);
        pend_qb = (int)pqb;
        epi_pending = false;
      }
      pack_p();
      if (last_in_tile) {
        if (pend_qb >= 0 && (uint32_t)pend_qb == qbn) {
          if (wtid == 0) { tma_store_wait_read0(); mbar_arrive(q_empty + 8 * pend_qb); }
          pend_qb = -1;
        }
        mbar_wait(q_full + 8 * qbn, ((tl + 1) >> 1) & 1);
      }
      mbar_wait(v_full + 8 * stc, phc);
      TL2();
      named_bar_sync(BAR_PP0 + cw, 256);
      TL2();
      wgmma_fence();
      {
        const uint64_t dq = dQ0 + qbn * TILE16, dk = dK0 + stn * TILE16;
#pragma unroll
        for (int ks = 0; ks < 8; ks++) {
          const uint64_t off = (uint64_t)(((ks >> 2) * 16384 + (ks & 3) * 32) >> 4);
          wgmma_m64n128k16_ss<0>(s, dq + off, dk + off, ks != 0);
        }
        wgmma_commit();
      }
      if (!first_in_tile) rescale_o();
      wgmma_fence();
      issue_pv(stc);
      named_bar_arrive(BAR_PP0 + (cw ^ 1), 256);
      TL2();
      wgmma_wait<1>();
      reg_fence(s);
      TL2();
      if (wtid == 0) {
        mbar_arrive(k_empty + 8 * stn);
        if (pend_qb >= 0) {
          tma_store_wait_read0();
          mbar_arrive(q_empty + 8 * pend_qb);
        }
      }
      pend_qb = -1;
      if (last_in_tile) {
        lp0 = l0; lp1 = l1; ph_ = h; pqi = qi; pqb = qb; epi_pending = true;
#pragma unroll
        for (int j = 0; j < 16; j++) {
          const int c = 8 * j + cq;
          if (c > r0) s[4 * j + 0] = -INFINITY;
          if (c + 1 > r0) s[4 * j + 1] = -INFINITY;
          if (c > r0 + 8) s[4 * j + 2] = -INFINITY;
          if (c + 1 > r0 + 8) s[4 * j + 3] = -INFINITY;
        }
        m0 = -INFINITY; m1 = -INFINITY; l0 = 0.f; l1 = 0.f;
      }
      attn_softmax(s, m0, m1, l0, l1, sc0, sc1, sl2);
      e++;
      first_in_tile = last_in_tile;
      if (last_in_tile) {
        tl++; h = nitem >> 4; qi = nitem & 15; n = qi;
        nitem = 0xFFFFu;
      } else {
        n--;
      }
      if (n == 0 && tl + 1 < AT_MAXPER) nitem = sched.item[blockIdx.x * AT_MAXPER + tl + 1];
    }
    {
      const uint32_t stc = e & 1, phc = (e >> 1) & 1;
      mbar_wait(v_full + 8 * stc, phc);
      wgmma_wait<0>();
      reg_fence_u(p);
      reg_fence(o);
      if (epi_pending) tile_epilogue(lp0, lp1, pqb, ph_, pqi);
      pack_p();
      named_bar_sync(BAR_PP0 + cw, 256);
      if (!first_in_tile) rescale_o();
      wgmma_fence();
      issue_pv(stc);
      named_bar_arrive(BAR_PP0 + (cw ^ 1), 256);
      wgmma_wait<0>();
      reg_fence(o);
      tile_epilogue(l0, l1, (uint32_t)(tl & 1), h, qi);
    }
    if (wtid == 0) tma_store_wait_all0();
  }
}

constexpr int G2_STAGES = 6;
constexpr int G2_A_BYTES = 128 * 64 * 2;
constexpr int G2_B_BYTES = 64 * 128 * 2;
constexpr int G2_STAGE_BYTES = G2_A_BYTES + G2_B_BYTES;
constexpr int G2_SMEM = G2_STAGES * G2_STAGE_BYTES + 256 + 1024;
constexpr int G2_KB_S = 32;
constexpr int G2_KB_F = 14;

struct G2Maps {
  CUtensorMap a_ctx, a_h;
  CUtensorMap b_wo, b_w2;
};

__global__ void __cluster_dims__(2, 1, 1) __launch_bounds__(384, 1)
gemm2_kernel(const __grid_constant__ G2Maps maps, const bf16* __restrict__ x, bf16* __restrict__ out) {
  extern __shared__ uint8_t smem_raw[];
  const uint32_t base = (smem_u32(smem_raw) + 1023u) & ~1023u;
  const uint32_t bar_full = base + G2_STAGES * G2_STAGE_BYTES;
  const uint32_t bar_empty = bar_full + 8 * G2_STAGES;
  const int tid = threadIdx.x;
  const int wg = tid >> 7;
  const int rank = blockIdx.x & 1;
  const int tile = blockIdx.x >> 1;
  const int mt = tile >> 2, nt = tile & 3;

  if (tid == 0) {
    for (int s = 0; s < G2_STAGES; s++) {
      mbar_init(bar_full + 8 * s, 1);
      mbar_init(bar_empty + 8 * s, 2);
    }
    fence_barrier_init();
  }
  __syncthreads();

  if (wg == 0) {
    setmaxnreg_dec<40>();
    if (tid == 0) {
      prefetch_tmap(&maps.a_ctx); prefetch_tmap(&maps.b_wo); prefetch_tmap(&maps.a_h); prefetch_tmap(&maps.b_w2);
      pdl_wait();
      for (uint32_t it = 0; it < (uint32_t)(G2_KB_S + G2_KB_F); it++) {
        const uint32_t s = it % G2_STAGES, ph = (it / G2_STAGES) & 1;
        mbar_wait(bar_empty + 8 * s, ph ^ 1);
        mbar_expect_tx(bar_full + 8 * s, G2_STAGE_BYTES);
        const uint32_t sa = base + s * G2_STAGE_BYTES;
        if (it < (uint32_t)G2_KB_S) {
          const int k0 = (rank * G2_KB_S + (int)it) * 64;
          tma_load_2d(sa, &maps.a_ctx, bar_full + 8 * s, k0, mt * 128);
          tma_load_3d(sa + G2_A_BYTES, &maps.b_wo, bar_full + 8 * s, 0, k0, nt * 2);
        } else {
          const int k0 = (rank * G2_KB_F + (int)it - G2_KB_S) * 64;
          tma_load_2d(sa, &maps.a_h, bar_full + 8 * s, k0, mt * 128);
          tma_load_3d(sa + G2_A_BYTES, &maps.b_w2, bar_full + 8 * s, 0, k0, nt * 2);
        }
      }
    }
    cluster_arrive(); cluster_wait();
    cluster_arrive(); cluster_wait();
  } else {
    setmaxnreg_inc<232>();
    const int cw = wg - 1;
    const int wtid = tid & 127;
    const int warp = wtid >> 5, lane = tid & 31;
    float acs[64], acf[64];
    uint32_t it = 0;
    for (int kb = 0; kb < G2_KB_S; kb++, it++) {
      const uint32_t s = it % G2_STAGES, ph = (it / G2_STAGES) & 1;
      mbar_wait(bar_full + 8 * s, ph);
      const uint32_t sa = base + s * G2_STAGE_BYTES;
      const uint64_t da = make_desc(sa + cw * 8192, 16, 1024);
      const uint64_t db = make_desc(sa + G2_A_BYTES, 8192, 1024);
      wgmma_fence();
#pragma unroll
      for (int ks = 0; ks < 4; ks++) wgmma_m64n128k16_ss<1>(acs, da + ks * 2, db + ks * 128, (kb | ks) != 0);
      wgmma_commit();
      if (kb > 0) {
        wgmma_wait<1>();
        if (wtid == 0) mbar_arrive(bar_empty + 8 * ((it - 1) % G2_STAGES));
      }
    }
    for (int kb = 0; kb < G2_KB_F; kb++, it++) {
      const uint32_t s = it % G2_STAGES, ph = (it / G2_STAGES) & 1;
      mbar_wait(bar_full + 8 * s, ph);
      const uint32_t sa = base + s * G2_STAGE_BYTES;
      const uint64_t da = make_desc(sa + cw * 8192, 16, 1024);
      const uint64_t db = make_desc(sa + G2_A_BYTES, 8192, 1024);
      wgmma_fence();
#pragma unroll
      for (int ks = 0; ks < 4; ks++) wgmma_m64n128k16_ss<1>(acf, da + ks * 2, db + ks * 128, (kb | ks) != 0);
      wgmma_commit();
      wgmma_wait<1>();
      if (wtid == 0) mbar_arrive(bar_empty + 8 * ((it - 1) % G2_STAGES));
    }
    wgmma_wait<0>();
    reg_fence(acs);
    reg_fence(acf);

    cluster_arrive(); cluster_wait();
    if (cw != rank) {
      uint32_t raddr;
      asm volatile("mapa.shared::cluster.u32 %0, %1, %2;" : "=r"(raddr) : "r"(base), "r"(rank ^ 1));
#pragma unroll
      for (int i = 0; i < 16; i++) {
        asm volatile("st.shared::cluster.v4.f32 [%0], {%1, %2, %3, %4};" ::"r"(raddr + (i * 128 + wtid) * 16),
                     "f"(acs[4 * i]), "f"(acs[4 * i + 1]), "f"(acs[4 * i + 2]), "f"(acs[4 * i + 3])
                     : "memory");
        asm volatile("st.shared::cluster.v4.f32 [%0], {%1, %2, %3, %4};" ::"r"(raddr + 32768 + (i * 128 + wtid) * 16),
                     "f"(acf[4 * i]), "f"(acf[4 * i + 1]), "f"(acf[4 * i + 2]), "f"(acf[4 * i + 3])
                     : "memory");
      }
    }
    cluster_arrive(); cluster_wait();
    if (cw == rank) {
      const int r0 = mt * 128 + cw * 64 + warp * 16 + (lane >> 2);
      const int cq = nt * 128 + (lane & 3) * 2;
#pragma unroll
      for (int i = 0; i < 16; i++) {
        float4 ps, pf;
        asm volatile("ld.shared.v4.f32 {%0, %1, %2, %3}, [%4];" : "=f"(ps.x), "=f"(ps.y), "=f"(ps.z), "=f"(ps.w)
                     : "r"(base + (i * 128 + wtid) * 16));
        asm volatile("ld.shared.v4.f32 {%0, %1, %2, %3}, [%4];" : "=f"(pf.x), "=f"(pf.y), "=f"(pf.z), "=f"(pf.w)
                     : "r"(base + 32768 + (i * 128 + wtid) * 16));
        float sv[4] = {acs[4 * i] + ps.x, acs[4 * i + 1] + ps.y, acs[4 * i + 2] + ps.z, acs[4 * i + 3] + ps.w};
        float fv[4] = {acf[4 * i] + pf.x, acf[4 * i + 1] + pf.y, acf[4 * i + 2] + pf.z, acf[4 * i + 3] + pf.w};
#pragma unroll
        for (int hh = 0; hh < 2; hh++) {
          const size_t off = (size_t)(r0 + hh * 8) * DM + cq + 8 * i;
          const __nv_bfloat162 xv = *reinterpret_cast<const __nv_bfloat162*>(x + off);
          float res[2];
#pragma unroll
          for (int c = 0; c < 2; c++) {
            const float sb = bf16_round(sv[hh * 2 + c]);
            const float fb = bf16_round(fv[hh * 2 + c]);
            const float g = bf16_round(__fdividef(fb, 1.0f + __expf(-fb)));
            const float pr = bf16_round(sb * g);
            res[c] = (c == 0 ? __bfloat162float(xv.x) : __bfloat162float(xv.y)) + pr;
          }
          *reinterpret_cast<uint32_t*>(out + off) = pack_bf16(res[0], res[1]);
        }
      }
    }
  }
}

typedef CUresult (*PFN_encodeTiled)(CUtensorMap*, CUtensorMapDataType, cuuint32_t, void*, const cuuint64_t*,
                                    const cuuint64_t*, const cuuint32_t*, const cuuint32_t*, CUtensorMapInterleave,
                                    CUtensorMapSwizzle, CUtensorMapL2promotion, CUtensorMapFloatOOBfill);

static PFN_encodeTiled get_encode() {
  static PFN_encodeTiled fn = nullptr;
  if (!fn) {
    void* p = nullptr;
    cudaDriverEntryPointQueryResult qr;
    cudaGetDriverEntryPoint("cuTensorMapEncodeTiled", &p, cudaEnableDefault, &qr);
    fn = (PFN_encodeTiled)p;
  }
  return fn;
}

static void make_map_2d(CUtensorMap* m, const void* ptr, uint64_t cols, uint64_t rows, uint32_t bc, uint32_t br) {
  cuuint64_t dims[2] = {cols, rows};
  cuuint64_t strides[1] = {cols * 2};
  cuuint32_t box[2] = {bc, br};
  cuuint32_t es[2] = {1, 1};
  get_encode()(m, CU_TENSOR_MAP_DATA_TYPE_BFLOAT16, 2, const_cast<void*>(ptr), dims, strides, box, es,
               CU_TENSOR_MAP_INTERLEAVE_NONE, CU_TENSOR_MAP_SWIZZLE_128B, CU_TENSOR_MAP_L2_PROMOTION_L2_128B,
               CU_TENSOR_MAP_FLOAT_OOB_FILL_NONE);
}
static void make_map_3d(CUtensorMap* m, const void* ptr, uint64_t cols, uint64_t rows, uint32_t br, uint32_t nchunk) {
  cuuint64_t dims[3] = {64, rows, cols / 64};
  cuuint64_t strides[2] = {cols * 2, 128};
  cuuint32_t box[3] = {64, br, nchunk};
  cuuint32_t es[3] = {1, 1, 1};
  get_encode()(m, CU_TENSOR_MAP_DATA_TYPE_BFLOAT16, 3, const_cast<void*>(ptr), dims, strides, box, es,
               CU_TENSOR_MAP_INTERLEAVE_NONE, CU_TENSOR_MAP_SWIZZLE_128B, CU_TENSOR_MAP_L2_PROMOTION_L2_128B,
               CU_TENSOR_MAP_FLOAT_OOB_FILL_NONE);
}

static void build_attn_schedule(AtSched* sc) {
  int load[132];
  int cnt[132];
  for (int i = 0; i < 132; i++) { load[i] = 0; cnt[i] = 0; }
  for (int i = 0; i < 132 * AT_MAXPER; i++) sc->item[i] = 0xFFFF;
  for (int qi = 15; qi >= 0; qi--) {
    for (int h = 0; h < NH; h++) {
      int best = 0;
      for (int c = 1; c < 132; c++)
        if (load[c] < load[best]) best = c;
      sc->item[best * AT_MAXPER + cnt[best]] = (uint16_t)((h << 4) | qi);
      cnt[best]++;
      load[best] += qi + 1;
    }
  }
}

extern "C" void kernel_launch(void* const* d_in, const int* in_sizes, int n_in, void* d_out, int out_size) {
  const bf16* x = (const bf16*)d_in[0];
  const bf16* ckv = (const bf16*)d_in[1];
  const bf16* wq = (const bf16*)d_in[2];
  const bf16* wuk = (const bf16*)d_in[3];
  const bf16* wuv = (const bf16*)d_in[4];
  const bf16* wo = (const bf16*)d_in[5];
  const bf16* w1 = (const bf16*)d_in[7];
  const bf16* w2 = (const bf16*)d_in[8];
  bf16* out = (bf16*)d_out;

  void *p_xn, *p_q, *p_k, *p_v, *p_h, *p_ctx;
  cudaGetSymbolAddress(&p_xn, g_xn);
  cudaGetSymbolAddress(&p_q, g_q);
  cudaGetSymbolAddress(&p_k, g_k);
  cudaGetSymbolAddress(&p_v, g_v);
  cudaGetSymbolAddress(&p_h, g_h);
  cudaGetSymbolAddress(&p_ctx, g_ctx);

  static bool attr_done = false;
  if (!attr_done) {
    cudaFuncSetAttribute(gemm1_kernel, cudaFuncAttributeMaxDynamicSharedMemorySize, G1_SMEM);
    cudaFuncSetAttribute(attn_kernel, cudaFuncAttributeMaxDynamicSharedMemorySize, AT_SMEM);
    cudaFuncSetAttribute(gemm2_kernel, cudaFuncAttributeMaxDynamicSharedMemorySize, G2_SMEM);
    attr_done = true;
  }

  G1Maps g1;
  make_map_2d(&g1.a[0], ckv, DM, SEQ, 64, 128);
  make_map_2d(&g1.a[1], p_xn, DM, SEQ, 64, 128);
  make_map_3d(&g1.b[0], wuk, NH * HD, DM, 64, 2);
  make_map_3d(&g1.b[1], wuv, NH * HD, DM, 64, 2);
  make_map_3d(&g1.b[2], wq, NH * HD, DM, 64, 2);
  make_map_3d(&g1.b[3], w1, DFF, DM, 64, 2);
  make_map_2d(&g1.c[0], p_k, HD, NH * SEQ, 64, 16);
  make_map_2d(&g1.c[1], p_v, HD, NH * SEQ, 64, 16);
  make_map_2d(&g1.c[2], p_q, HD, NH * SEQ, 64, 16);
  make_map_2d(&g1.c[3], p_h, DFF, SEQ, 64, 16);

  AtMaps am;
  make_map_3d(&am.q, p_q, HD, NH * SEQ, 128, 2);
  make_map_3d(&am.k, p_k, HD, NH * SEQ, 128, 2);
  make_map_3d(&am.v, p_v, HD, NH * SEQ, 128, 2);
  make_map_2d(&am.o, p_ctx, NH * HD, SEQ, 64, 64);
  static AtSched sched;
  static bool sched_done = false;
  if (!sched_done) { build_attn_schedule(&sched); sched_done = true; }

  G2Maps g2;
  make_map_2d(&g2.a_ctx, p_ctx, NH * HD, SEQ, 64, 128);
  make_map_2d(&g2.a_h, p_h, DFF, SEQ, 64, 128);
  make_map_3d(&g2.b_wo, wo, DM, NH * HD, 64, 2);
  make_map_3d(&g2.b_w2, w2, DM, DFF, 64, 2);

  cudaStream_t st = cudaStreamPerThread;
  ln_kernel<<<SEQ / 8, 256, 0, st>>>(x, (bf16*)p_xn);
  {
    cudaLaunchAttribute at[1];
    at[0].id = cudaLaunchAttributeProgrammaticStreamSerialization;
    at[0].val.programmaticStreamSerializationAllowed = 1;
    cudaLaunchConfig_t cfg = {};
    cfg.stream = st; cfg.attrs = at; cfg.numAttrs = 1;
    cfg.gridDim = dim3(132); cfg.blockDim = dim3(384); cfg.dynamicSmemBytes = G1_SMEM;
    cudaLaunchKernelEx(&cfg, gemm1_kernel, g1);
    cfg.gridDim = dim3(132); cfg.blockDim = dim3(384); cfg.dynamicSmemBytes = AT_SMEM;
    cudaLaunchKernelEx(&cfg, attn_kernel, am, sched);
    cfg.gridDim = dim3(128); cfg.blockDim = dim3(384); cfg.dynamicSmemBytes = G2_SMEM;
    cudaLaunchKernelEx(&cfg, gemm2_kernel, g2, x, out);
  }
}
```
